```python
import torch

def _softmax(x, axis=-1):
    return torch.softmax(x, dim=axis)
def _gelu(x):
    return torch.nn.functional.gelu(x, approximate="tanh")
def _silu(x):
    return torch.nn.functional.silu(x)
def _sigmoid(x):
    return torch.sigmoid(x)
def _layernorm(x, axis=-1, eps=1e-5):
    m = x.mean(dim=axis, keepdim=True)
    v = x.var(dim=axis, keepdim=True, unbiased=False)
    return (x - m) / torch.sqrt(v + eps)
def _scatter_add(tgt, idx, src, axis=0):
    return tgt.clone().index_add_(axis, idx, src)
def _segment_sum(src, seg, n):
    out = torch.zeros((n,) + src.shape[1:], dtype=src.dtype)
    return out.index_add_(0, seg, src)
def _pad(x, pw):
    flat = tuple(v for pair in reversed(pw) for v in pair)
    return torch.nn.functional.pad(x, flat)

kernel_name = 'standalone__cheap_equivariant_egnn__graph'

def setup_inputs():

    _w = (lambda a: (lambda t: t.to(torch.bfloat16) if t.is_floating_point() else t)(torch.as_tensor(a)))
    N, deg, D, De = 50000, 16, 64, max(0, 1)
    E = N * deg
    return {
        "h": _w((lambda *s: torch.randn(*s, dtype=torch.bfloat16) * 0.2)(N, D)),
        "pos": _w((lambda *s: torch.randn(*s, dtype=torch.bfloat16) * 0.4)(N, 3)),
        "e_attr": _w((lambda *s: torch.randn(*s, dtype=torch.bfloat16) * 0.4)(E, De)),
        "src": _w((lambda lo, hi, *s: torch.randint(lo, hi, s))(0, N, E).to(torch.int64)),
        "dst": _w((lambda lo, hi, *s: torch.randint(lo, hi, s))(0, N, E).to(torch.int64)),
        "w_e": _w(0.1 * (lambda *s: torch.randn(*s, dtype=torch.bfloat16) * 0.4)(2 * D + 1 + De, D)),
        "w_x": _w(0.1 * (lambda *s: torch.randn(*s, dtype=torch.bfloat16) * 0.2)(D, 1)),
        "w_h": _w(0.1 * (lambda *s: torch.randn(*s, dtype=torch.bfloat16) * 0.2)(2 * D, D)),
    }

def reference(h, pos, e_attr, src, dst, w_e, w_x, w_h):
    N, D = h.shape[0], h.shape[1]
    diff = pos[dst] - pos[src]
    dist2 = torch.sum(diff * diff, axis=-1, keepdims=True)
    e_in = torch.concatenate([h[dst], h[src], dist2, e_attr], axis=-1)
    m_ij = _silu(e_in @ w_e)
    coord_scale = m_ij @ w_x
    pos_new = pos + _segment_sum(diff * coord_scale, dst, N)
    m_i = _segment_sum(m_ij, dst, N)
    h_new = h + _silu(torch.concatenate([h, m_i], axis=-1) @ w_h)
    return h_new, pos_new
```

```cpp
#include <cuda_runtime.h>
#include <cuda_bf16.h>
#include <stdint.h>
#include <type_traits>

namespace {

constexpr int NN = 50000;
constexpr int EE = 800000;
constexpr int NB = 132;
constexpr int NPB = 379;
constexpr int EPB = 6064;
constexpr int NWE = 12;
constexpr int NWC = 11;
constexpr int NTE = NWE * 32;
constexpr int NW = NWE + 4;
constexpr int NT = NW * 32;
constexpr int RND = (EPB / 4 + NTE - 1) / NTE;
constexpr int RP = 3168;
constexpr int NG = 48;
constexpr int CAPD = 50;
constexpr int NSEG = 12;
constexpr int NRD = 10;
#define HWIN 4
#define POLLSLEEP 100
#define SENTMODE 1000
#define DELAY_SRC 0
#define HFIRST 0
#define GO_EARLY 1
#define BQ_ 8
#define PQ_ 1
constexpr int BQ = BQ_;
constexpr int PQ = PQ_;
#define BH1 ""
#define BH2 ".L1::evict_first"
#define POSOUT 0
#define XMASK "0xffff"
#define XPM "%13"
#define XNOUPD 0
constexpr unsigned SPIN_LIMIT = 1u << 24;

constexpr int SM_W2 = 0;
constexpr int SM_H = SM_W2 + 8192;
constexpr int SM_U = SM_H + 49152;
constexpr int SM_W = SM_U + 24576;
constexpr int SM_SLOT = SM_U + 49152;
constexpr int SM_SRC = SM_U;
constexpr int SM_EA = SM_SLOT + 52224;
constexpr int SM_HIST = SM_SLOT + 384 * CAPD * 4;
constexpr int SM_DH = SM_HIST + 160 * 4;
constexpr int SM_MISC = SM_DH + 64 * 4;
constexpr int SM_CUR = SM_MISC + 64;
constexpr int SM_ORD = SM_CUR + 416 * 4;
constexpr int SM_POS = SM_ORD + 384 * 4;
constexpr int SM_CONST = SM_POS + 384 * 8;
constexpr int SM_TAG = SM_CONST + 3072;
constexpr int SM_TOTAL = SM_TAG + 64;
static_assert(2 * RP >= EPB + 2 * NB && (RND * NTE * 4 + 320) * 8 <= SM_EA - SM_SLOT && SM_EA + RND * NTE * 8 <= SM_HIST &&
              RND * NTE * 16 <= SM_W - SM_SRC && (RND - 1) * NTE * 4 <= EE - (NB - 1) * EPB, "edge rounds");
static_assert(NG == 3 * NW && NWE % 4 == 0 && CAPD % 2 == 0 && CAPD <= 62 && (SM_CUR - SM_HIST) == 60 * 16 && SM_W % 1024 == 0, "work split");
static_assert(NN - (NB - 1) * NPB > 320 && SM_TAG % 8 == 0 && SM_TOTAL <= 232448 && NWC * NSEG == NB && NTE == 384, "layout");

struct Scratch {
    uint4 B[NB * 384 * BQ];
    uint4 rec[NB * RP];
    uint2 pos[NB * 384 * PQ];
    uint2 flag[NB * 160];
    uint32_t sync[32];
    float acc[NB * 384 * 68];
};
__device__ __align__(1024) Scratch g_scratch;

#define STAMPW(w, i)
#define DBG_SMEM 0
#define STAMP(i) STAMPW(0, i)

__device__ __forceinline__ uint32_t smem_u32(const void* p) { return (uint32_t)__cvta_generic_to_shared(p); }

__device__ __forceinline__ void mma16_acc(float (&d)[4], uint32_t a0, uint32_t a1, uint32_t a2, uint32_t a3,
                                          uint32_t b0, uint32_t b1) {
    asm("mma.sync.aligned.m16n8k16.row.col.f32.bf16.bf16.f32 {%0,%1,%2,%3}, {%4,%5,%6,%7}, {%8,%9}, {%0,%1,%2,%3};"
        : "+f"(d[0]), "+f"(d[1]), "+f"(d[2]), "+f"(d[3])
        : "r"(a0), "r"(a1), "r"(a2), "r"(a3), "r"(b0), "r"(b1));
}
__device__ __forceinline__ void mma8_acc(float (&d)[4], uint32_t a0, uint32_t a1, uint32_t b0) {
    asm("mma.sync.aligned.m16n8k8.row.col.f32.bf16.bf16.f32 {%0,%1,%2,%3}, {%4,%5}, {%6}, {%0,%1,%2,%3};"
        : "+f"(d[0]), "+f"(d[1]), "+f"(d[2]), "+f"(d[3])
        : "r"(a0), "r"(a1), "r"(b0));
}
__device__ __forceinline__ void mma8(float (&d)[4], uint32_t a0, uint32_t a1, uint32_t b0, const float (&c)[4]) {
    asm("mma.sync.aligned.m16n8k8.row.col.f32.bf16.bf16.f32 {%0,%1,%2,%3}, {%4,%5}, {%6}, {%7,%8,%9,%10};"
        : "=f"(d[0]), "=f"(d[1]), "=f"(d[2]), "=f"(d[3])
        : "r"(a0), "r"(a1), "r"(b0), "f"(c[0]), "f"(c[1]), "f"(c[2]), "f"(c[3]));
}
__device__ __forceinline__ void wgmma64(float (&d)[32], uint64_t da, uint64_t db, int acc) {
    asm volatile("{\n\t.reg .pred p;\n\tsetp.ne.b32 p, %34, 0;\n\t"
                 "wgmma.mma_async.sync.aligned.m64n64k16.f32.bf16.bf16 "
                 "{%0,%1,%2,%3,%4,%5,%6,%7,%8,%9,%10,%11,%12,%13,%14,%15,%16,%17,%18,%19,%20,%21,%22,%23,%24,%25,%26,%27,%28,%29,%30,%31}, "
                 "%32, %33, p, 1, 1, 0, 1;\n\t}"
                 : "+f"(d[0]), "+f"(d[1]), "+f"(d[2]), "+f"(d[3]), "+f"(d[4]), "+f"(d[5]), "+f"(d[6]), "+f"(d[7]),
                   "+f"(d[8]), "+f"(d[9]), "+f"(d[10]), "+f"(d[11]), "+f"(d[12]), "+f"(d[13]), "+f"(d[14]), "+f"(d[15]),
                   "+f"(d[16]), "+f"(d[17]), "+f"(d[18]), "+f"(d[19]), "+f"(d[20]), "+f"(d[21]), "+f"(d[22]), "+f"(d[23]),
                   "+f"(d[24]), "+f"(d[25]), "+f"(d[26]), "+f"(d[27]), "+f"(d[28]), "+f"(d[29]), "+f"(d[30]), "+f"(d[31])
                 : "l"(da), "l"(db), "r"(acc));
}
__device__ __forceinline__ uint64_t wg_desc(uint32_t addr) {
    return (uint64_t)((addr & 0x3ffff) >> 4) | ((uint64_t)1 << 16) | ((uint64_t)64 << 32) | ((uint64_t)1 << 62);
}
__device__ __forceinline__ void ldsm4t(uint32_t (&r)[4], uint32_t addr) {
    asm volatile("ldmatrix.sync.aligned.m8n8.x4.trans.shared.b16 {%0,%1,%2,%3}, [%4];"
                 : "=r"(r[0]), "=r"(r[1]), "=r"(r[2]), "=r"(r[3]) : "r"(addr));
}
__device__ __forceinline__ uint32_t movm(uint32_t a) {
    uint32_t d;
    asm("movmatrix.sync.aligned.m8n8.trans.b16 %0, %1;" : "=r"(d) : "r"(a));
    return d;
}
__device__ __forceinline__ uint32_t pack_bf16(float lo, float hi) {
    uint32_t r;
    asm("cvt.rn.bf16x2.f32 %0, %1, %2;" : "=r"(r) : "f"(hi), "f"(lo));
    return r;
}
__device__ __forceinline__ float tanh_fast(float x) {
    float y;
    asm("tanh.approx.f32 %0, %1;" : "=f"(y) : "f"(x));
    return y;
}
__device__ __forceinline__ float silu_half(float hx) { return fmaf(hx, tanh_fast(hx), hx); }
__device__ __forceinline__ uint32_t hadd2_bf16(uint32_t a, uint32_t b) {
    uint32_t r;
    asm("add.rn.bf16x2 %0, %1, %2;" : "=r"(r) : "r"(a), "r"(b));
    return r;
}
__device__ __forceinline__ uint32_t hsub2_bf16(uint32_t a, uint32_t b) {
    uint32_t r;
    asm("sub.rn.bf16x2 %0, %1, %2;" : "=r"(r) : "r"(a), "r"(b));
    return r;
}
__device__ __forceinline__ uint32_t hmul2_bf16(uint32_t a, uint32_t b) {
    uint32_t r;
    asm("mul.rn.bf16x2 %0, %1, %2;" : "=r"(r) : "r"(a), "r"(b));
    return r;
}
__device__ __forceinline__ float bf_lo(uint32_t v) { return __uint_as_float(v << 16); }
__device__ __forceinline__ float bf_hi(uint32_t v) { return __uint_as_float(v & 0xffff0000u); }
__device__ __forceinline__ uint32_t half_bf16x2(uint32_t v) { return hmul2_bf16(v, 0x3f003f00u); }
template <typename T> __device__ __forceinline__ T opaque(T v) { asm volatile("" : "+r"(v)); return v; }

__device__ __forceinline__ uint32_t ld_relaxed(const uint32_t* p) {
    uint32_t v;
    asm volatile("ld.relaxed.gpu.global.u32 %0, [%1];" : "=r"(v) : "l"(p) : "memory");
    return v;
}
__device__ __forceinline__ uint2 ld_relaxed64(const uint2* p) {
    unsigned long long v;
    asm volatile("ld.relaxed.gpu.global.u64 %0, [%1];" : "=l"(v) : "l"(p) : "memory");
    return make_uint2((uint32_t)v, (uint32_t)(v >> 32));
}
__device__ __forceinline__ uint4 ld_relaxed2x64(const uint4* p) {
    unsigned long long a, b;
    asm volatile("ld.relaxed.gpu.global.v2.u64 {%0,%1}, [%2];" : "=l"(a), "=l"(b) : "l"(p) : "memory");
    return make_uint4((uint32_t)a, (uint32_t)(a >> 32), (uint32_t)b, (uint32_t)(b >> 32));
}
__device__ __forceinline__ uint32_t atoms_add(uint32_t addr, uint32_t v) {
    uint32_t r;
    asm volatile("atom.shared.add.u32 %0, [%1], %2;" : "=r"(r) : "r"(addr), "r"(v) : "memory");
    return r;
}
__device__ __forceinline__ uint32_t lds_u32(uint32_t addr) {
    uint32_t v;
    asm volatile("ld.shared.u32 %0, [%1];" : "=r"(v) : "r"(addr) : "memory");
    return v;
}
__device__ __forceinline__ void sts_u32(uint32_t addr, uint32_t v) { asm volatile("st.shared.u32 [%0], %1;" :: "r"(addr), "r"(v) : "memory"); }
__device__ __forceinline__ void sts_u64(uint32_t addr, uint32_t x, uint32_t y) {
    asm volatile("st.shared.v2.u32 [%0], {%1,%2};" :: "r"(addr), "r"(x), "r"(y) : "memory");
}
__device__ __forceinline__ void st_relaxed64(uint2* p, uint32_t lo, uint32_t hi) {
    asm volatile("st.relaxed.gpu.global.u64 [%0], %1;" :: "l"(p), "l"((unsigned long long)lo | ((unsigned long long)hi << 32)) : "memory");
}
__device__ __forceinline__ void st_relaxed(uint32_t* p, uint32_t v) {
    asm volatile("st.relaxed.gpu.global.u32 [%0], %1;" :: "l"(p), "r"(v) : "memory");
}
__device__ __forceinline__ void fence_gpu() { asm volatile("fence.acq_rel.gpu;" ::: "memory"); }
__device__ __forceinline__ void fence_async_smem() { asm volatile("fence.proxy.async.shared::cta;" ::: "memory"); }
__device__ __forceinline__ void bar_sync(int id, int n) { asm volatile("bar.sync %0, %1;" :: "r"(id), "r"(n) : "memory"); }
__device__ __forceinline__ void bar_arrive(int id, int n) { asm volatile("bar.arrive %0, %1;" :: "r"(id), "r"(n) : "memory"); }

__device__ __forceinline__ void bulk_s2g(void* dst, uint32_t src, uint32_t bytes) {
    asm volatile("cp.async.bulk.global.shared::cta.bulk_group [%0], [%1], %2;" :: "l"(dst), "r"(src), "r"(bytes) : "memory");
    asm volatile("cp.async.bulk.commit_group;" ::: "memory");
}
__device__ __forceinline__ void bulk_wait() { asm volatile("cp.async.bulk.wait_group 0;" ::: "memory"); }

__device__ __forceinline__ uint32_t lds_u16(uint32_t addr) {
    uint32_t v;
    asm volatile("ld.shared.u16 %0, [%1];" : "=r"(v) : "r"(addr));
    return v;
}
__device__ __forceinline__ int4 ldg_stream4(const void* p) {
    int4 v;
    asm volatile("ld.global.L1::no_allocate.v4.u32 {%0,%1,%2,%3}, [%4];" : "=r"(v.x), "=r"(v.y), "=r"(v.z), "=r"(v.w) : "l"(p));
    return v;
}
__device__ __forceinline__ uint2 ldg_stream2(const void* p) {
    uint2 v;
    asm volatile("ld.global.L1::no_allocate.v2.u32 {%0,%1}, [%2];" : "=r"(v.x), "=r"(v.y) : "l"(p));
    return v;
}

__device__ __forceinline__ uint4* srow(unsigned char* tile, int row, int t, int half) {
    return reinterpret_cast<uint4*>(tile + row * 128) + (t + (((row ^ half) & 1) << 2));
}
__device__ __forceinline__ void load_srow(uint32_t (&r)[8], unsigned char* tile, int row, int t) {
    const uint4 u = *srow(tile, row, t, 0), v = *srow(tile, row, t, 1);
    r[0] = u.x; r[1] = u.y; r[2] = u.z; r[3] = u.w; r[4] = v.x; r[5] = v.y; r[6] = v.z; r[7] = v.w;
}

__device__ __forceinline__ void node_update(unsigned char* smem, uint32_t (&m)[8], int n, int nvalid, int node0,
                                            uint32_t ident, const __nv_bfloat16* __restrict__ h,
                                            __nv_bfloat16* __restrict__ out) {
    const int lane = threadIdx.x & 31, t = lane & 3, i = lane & 7;
    const uint4* hp = reinterpret_cast<const uint4*>(h + (size_t)(node0 + min(n, nvalid - 1)) * 64) + t;
    const uint4 h0 = __ldg(hp), h1 = __ldg(hp + 4);
    const uint32_t wl = smem_u32(smem) + SM_W2 + (8 * (i >> 1) + 2 * (lane >> 4) + (i & 1)) * 128 + (((((lane >> 3) & 1) ^ i)) << 4);
    uint32_t ur[8];
    load_srow(ur, smem + SM_U, n, t);
    float o[4][4];
#pragma unroll
    for (int mt = 0; mt < 4; mt++) {
        o[mt][0] = o[mt][1] = o[mt][2] = o[mt][3] = 0.f;
        mma16_acc(o[mt], ident, 0u, 0u, ident, ur[2 * mt], ur[2 * mt + 1]);
    }
#pragma unroll
    for (int kk = 0; kk < 4; kk++)
#pragma unroll
        for (int mt = 0; mt < 4; mt++) {
            uint32_t w[4];
            ldsm4t(w, (wl ^ (mt << 5)) + (4 * (kk & 1) + 32 * (kk >> 1)) * 128);
            mma16_acc(o[mt], w[0], w[1], w[2], w[3], m[2 * kk], m[2 * kk + 1]);
        }
    const uint32_t hr[8] = {h0.x, h0.y, h0.z, h0.w, h1.x, h1.y, h1.z, h1.w};
#pragma unroll
    for (int j = 0; j < 4; j++) {
        m[2 * j] = hadd2_bf16(hr[2 * j], movm(pack_bf16(silu_half(o[j][0]), silu_half(o[j][1]))));
        m[2 * j + 1] = hadd2_bf16(hr[2 * j + 1], movm(pack_bf16(silu_half(o[j][2]), silu_half(o[j][3]))));
    }
    if (n < nvalid) {
        uint4* p = reinterpret_cast<uint4*>(out + (size_t)(node0 + n) * 64) + t;
        p[0] = make_uint4(m[0], m[1], m[2], m[3]);
        p[4] = make_uint4(m[4], m[5], m[6], m[7]);
    }
}

__device__ __noinline__ void slow_path(Scratch* sc, unsigned char* smem, const __nv_bfloat16* __restrict__ h,
                                       const __nv_bfloat16* __restrict__ pos,
                                       const __nv_bfloat16* __restrict__ eattr, const int* __restrict__ src,
                                       const int* __restrict__ dst, const __nv_bfloat16* __restrict__ w_e,
                                       const __nv_bfloat16* __restrict__ w_x, __nv_bfloat16* __restrict__ out,
                                       int node0, int nvalid, uint32_t ident) {
    const int tid = threadIdx.x, lane = tid & 31, warp = tid >> 5, g = lane >> 2, t = lane & 3;
    float* acc = sc->acc + blockIdx.x * 384 * 68;
    for (int i = tid; i < 384 * 68; i += NT) __stcg(acc + i, 0.f);
    __threadfence();
    __syncthreads();
    const uint32_t* sA = reinterpret_cast<const uint32_t*>(smem + SM_H);
    const __nv_bfloat16* sP = reinterpret_cast<const __nv_bfloat16*>(smem + SM_POS);
    const unsigned short* pos16 = reinterpret_cast<const unsigned short*>(pos);
    const float wd0 = __bfloat162float(w_e[128 * 64 + 2 * lane]), wd1 = __bfloat162float(w_e[128 * 64 + 2 * lane + 1]);
    const float wa0 = __bfloat162float(w_e[129 * 64 + 2 * lane]), wa1 = __bfloat162float(w_e[129 * 64 + 2 * lane + 1]);
    const float wx0 = __bfloat162float(w_x[2 * lane]), wx1 = __bfloat162float(w_x[2 * lane + 1]);
    for (int eb = warp * 32; eb < EE; eb += NT) {
        const int dv = dst[eb + lane] - node0;
        unsigned mask = __ballot_sync(~0u, dv >= 0 && dv < nvalid);
        while (mask) {
            const int l = __ffs(mask) - 1;
            mask &= mask - 1;
            const int dl = __shfl_sync(~0u, dv, l);
            const int s = src[eb + l];
            const uint32_t av = sA[dl * 32 + (lane ^ ((dl & 1) << 4))];
            const uint32_t bv = __ldcg(reinterpret_cast<const uint32_t*>(sc->B) + (size_t)s * (BQ * 4) + ((lane >> 2) & 3) * 8 + (lane >> 4) * 4 + (lane & 3));
            const uint32_t pdxy = *reinterpret_cast<const uint32_t*>(sP + dl * 4);
            const uint32_t pdz = *reinterpret_cast<const uint32_t*>(sP + dl * 4 + 2);
            const uint32_t psxy = pos16[s * 3] | ((uint32_t)pos16[s * 3 + 1] << 16), psz = pos16[s * 3 + 2];
            const uint32_t dxy = hsub2_bf16(pdxy, psxy), dz = hsub2_bf16(pdz, psz);
            const uint32_t sxy = hmul2_bf16(dxy, dxy), sz = hmul2_bf16(dz, dz);
            const float d2 = bf_lo(sxy) + bf_hi(sxy) + bf_lo(sz);
            const float ev = __bfloat162float(eattr[eb + l]);
            const float h0 = 0.5f * (d2 * wd0 + ev * wa0) + bf_lo(bv) + bf_lo(av);
            const float h1 = 0.5f * (d2 * wd1 + ev * wa1) + bf_hi(bv) + bf_hi(av);
            const uint32_t mp = pack_bf16(silu_half(h0), silu_half(h1));
            float cs = bf_lo(mp) * wx0 + bf_hi(mp) * wx1;
#pragma unroll
            for (int o = 16; o >= 1; o >>= 1) cs += __shfl_xor_sync(~0u, cs, o);
            atomicAdd(&acc[dl * 68 + 2 * lane], bf_lo(mp));
            atomicAdd(&acc[dl * 68 + 2 * lane + 1], bf_hi(mp));
            if (lane < 3) atomicAdd(&acc[dl * 68 + 64 + lane], cs * (lane == 0 ? bf_lo(dxy) : lane == 1 ? bf_hi(dxy) : bf_lo(dz)));
        }
    }
    __threadfence();
    __syncthreads();
    for (int i = tid; i < nvalid * 3; i += NT)
        out[(size_t)NN * 64 + node0 * 3 + i] = __float2bfloat16(__bfloat162float(sP[(i / 3) * 4 + i % 3]) + __ldcg(acc + (i / 3) * 68 + 64 + i % 3));
    for (int gi = warp; gi < NG; gi += NW) {
        const int n = gi * 8 + g;
        uint32_t m[8];
#pragma unroll
        for (int j = 0; j < 8; j++) {
            const int f = 8 * t + 2 * (j & 3) + 32 * (j >> 2);
            m[j] = pack_bf16(__ldcg(acc + n * 68 + f), __ldcg(acc + n * 68 + f + 1));
        }
        node_update(smem, m, n, nvalid, node0, ident, h, out);
    }
}

constexpr int BAR_E = 1;
constexpr int BAR_GO = 2;
constexpr int BAR_FREE = 3;
constexpr int BAR_S1 = 4;
constexpr int BAR_C = 5;
constexpr int BAR_B = 6;
constexpr int BAR_PRIO = 8;
constexpr int BAR_G = 7;

__global__ void __launch_bounds__(NT, 1)
egnn_kernel(const __nv_bfloat16* __restrict__ h, const __nv_bfloat16* __restrict__ pos,
            const __nv_bfloat16* __restrict__ eattr, const int* __restrict__ src, const int* __restrict__ dst,
            const __nv_bfloat16* __restrict__ w_e, const __nv_bfloat16* __restrict__ w_x,
            const __nv_bfloat16* __restrict__ w_h, __nv_bfloat16* __restrict__ out, Scratch* sc) {
    extern __shared__ __align__(1024) unsigned char smem[];
    const int tid = threadIdx.x, lane = tid & 31, warp = tid >> 5;
    const int g = lane >> 2, t = lane & 3;
    const int b = blockIdx.x;
    const int node0 = b * NPB;
    const int nvalid = min(NPB, NN - node0);
    const uint32_t sb = smem_u32(smem);

    uint32_t* sHist = reinterpret_cast<uint32_t*>(smem + SM_HIST);
    uint32_t* sCur = reinterpret_cast<uint32_t*>(smem + SM_CUR);
    uint32_t* sDh = reinterpret_cast<uint32_t*>(smem + SM_DH);
    uint32_t* sOrd = reinterpret_cast<uint32_t*>(smem + SM_ORD);
    uint32_t* sMisc = reinterpret_cast<uint32_t*>(smem + SM_MISC);
    uint32_t* sSlot = reinterpret_cast<uint32_t*>(smem + SM_SLOT);
    uint32_t* sTag = reinterpret_cast<uint32_t*>(smem + SM_TAG);
    STAMP(0);

    const int e0 = b * EPB;
    const int nchunk = (min(EPB, EE - e0)) >> 2;
    const int clast = min(tid + NTE * (RND - 1), nchunk - 1);
    const int4* wg = reinterpret_cast<const int4*>((warp & 2) ? w_h : w_e) + (warp & 1) * 512 + lane;
    int4 vd[RND];
#pragma unroll
    for (int j = 0; j < RND; j++)
        vd[j] = ldg_stream4(warp < NWE ? reinterpret_cast<const int4*>(dst + e0) + (j < RND - 1 ? tid + NTE * j : clast) : wg + 32 * j);

    int4 wv[12];
    if (warp >= NWE) {
#pragma unroll
        for (int j = 0; j < 12; j++) wv[j] = ldg_stream4(wg + 32 * (j + RND));
    }

    if (__builtin_expect(warp < NWE, 1)) {
        const uint32_t launch = ld_relaxed(&sc->sync[0]);
        if (tid < 60) reinterpret_cast<uint4*>(sHist)[tid] = make_uint4(0, 0, 0, 0);
        sCur[tid] = sb + SM_SLOT + tid * (CAPD * 4);
        if (tid < 32) sCur[384 + tid] = sb + SM_HIST;
#pragma unroll
        for (int j = 0; j < RND; j++) {
            const int c = j < RND - 1 ? tid + NTE * j : clast;
            asm volatile("cp.async.cg.shared.global [%0], [%1], 16;" :: "r"(sb + SM_SRC + (tid + NTE * j) * 16), "l"(reinterpret_cast<const int4*>(src + e0) + c) : "memory");
            asm volatile("cp.async.ca.shared.global [%0], [%1], 8;" :: "r"(sb + SM_EA + (tid + NTE * j) * 8), "l"(reinterpret_cast<const uint2*>(eattr + e0) + c) : "memory");
        }
        bar_sync(BAR_E, NTE);
        uint32_t ha[4 * RND], rk[4 * RND];
#pragma unroll
        for (int j = 0; j < RND; j++) {
            const int dv[4] = {vd[j].x, vd[j].y, vd[j].z, vd[j].w};
#pragma unroll
            for (int i = 0; i < 4; i++) {
                uint32_t own = __umulhi((uint32_t)dv[i], 11332368u);
                if (j == RND - 1 && tid + NTE * j >= nchunk) own = NB + (lane & 15);
                ha[j * 4 + i] = sb + SM_HIST + own * 4;
                rk[j * 4 + i] = atoms_add(ha[j * 4 + i], 8);
            }
        }
        STAMP(1);
        bar_arrive(BAR_GO, NT);
        const uint32_t tag = (launch % 0xffffu + 1) << 16, lid = launch + 1, target = lid * NB;
        unsigned spin = 0;
        auto poll_all = [&](int which) {
            while ((int)(ld_relaxed(&sc->sync[which]) - target) < 0 && ++spin < SPIN_LIMIT) __nanosleep(40);
        };
        auto count = [&](int which) { asm volatile("red.relaxed.gpu.global.add.u32 [%0], 1;" :: "l"(&sc->sync[which]) : "memory"); };
        if (warp == NWC) {
            bar_sync(BAR_S1, NTE);
            uint32_t c[5], pc[5], s = 0;
#pragma unroll
            for (int i = 0; i < 5; i++) { c[i] = sHist[lane * 5 + i]; pc[i] = max((c[i] + 8) & ~15u, 16u); s += pc[i]; }
            uint32_t inc = s;
#pragma unroll
            for (int o = 1; o < 32; o <<= 1) { const uint32_t v = __shfl_up_sync(~0u, inc, o); if (lane >= o) inc += v; }
            uint32_t off = inc - s;
#pragma unroll
            for (int i = 0; i < 5; i++) { sHist[lane * 5 + i] = sb + SM_SLOT + off; off += pc[i]; }
            bar_sync(BAR_E, NTE);
#pragma unroll
            for (int i = 4; i >= 0; i--) {
                off -= pc[i];
                if (lane * 5 + i < NB) st_relaxed64(sc->flag + (lane * 5 + i) * 160 + b, (off >> 4) | (pc[i] << 12), lid);
                const uint32_t pad = (((lane * 5 + i) * NPB + 383) & 0xffff) | tag;
                if (c[i] < pc[i]) sts_u64(sb + SM_SLOT + off + pc[i] - 8, 0, pad);
                if (c[i] == 0) sts_u64(sb + SM_SLOT + off, 0, pad);
            }
            __syncwarp();
            if (lane == 0) count(1);
        } else {
            bar_arrive(BAR_S1, NTE);
            bar_sync(BAR_E, NTE);
        }
        STAMP(2);
#pragma unroll
        for (int i = 0; i < 4 * RND; i++) rk[i] += lds_u32(ha[i]);
        asm volatile("cp.async.wait_all;" ::: "memory");
        STAMP(4);
        {
            int4 vs[RND];
            uint2 ve[RND];
#pragma unroll
            for (int j = 0; j < RND; j++) {
                vs[j] = reinterpret_cast<const int4*>(smem + SM_SRC)[tid + NTE * j];
                ve[j] = reinterpret_cast<const uint2*>(smem + SM_EA)[tid + NTE * j];
            }
#pragma unroll
            for (int j = 0; j < RND; j++) {
                sts_u64(rk[j * 4], __byte_perm(vs[j].x, ve[j].x, 0x5410), vd[j].x | tag);
                sts_u64(rk[j * 4 + 1], __byte_perm(vs[j].y, ve[j].x, 0x7610), vd[j].y | tag);
                sts_u64(rk[j * 4 + 2], __byte_perm(vs[j].z, ve[j].y, 0x5410), vd[j].z | tag);
                sts_u64(rk[j * 4 + 3], __byte_perm(vs[j].w, ve[j].y, 0x7610), vd[j].w | tag);
            }
        }
        fence_async_smem();
        STAMP(3);
        if (warp == NWC) {
            bar_sync(BAR_S1, NTE);
            if (lane == 0) bulk_s2g(sc->rec + b * RP, sb + SM_SLOT, sHist[NB] - (sb + SM_SLOT));
            __syncwarp();
            bar_arrive(BAR_PRIO, 160);
            if (lane == 0) bulk_wait();
            __syncwarp();
            bar_arrive(BAR_FREE, NTE);
            STAMPW(NWC, 17);
            bar_sync(BAR_B, 160);
            if (lane == 0) {
                fence_gpu();
                count(2);
                STAMPW(NWC, 18);
                poll_all(2);
                fence_gpu();
                if (b == 0) st_relaxed(&sc->sync[0], lid);
            }
            STAMPW(NWC, 19);
        } else {
            bar_arrive(BAR_S1, NTE);
            if (warp == 0) poll_all(1);
            bar_sync(BAR_C, NWC * 32);
            STAMP(23);
            const uint2* fp = sc->flag + b * 160 + warp * NSEG + min(lane, NSEG - 1);
            uint2 fv;
            do { fv = ld_relaxed64(fp); } while (__any_sync(~0u, fv.y != lid) && ++spin < SPIN_LIMIT);
            STAMP(22);
            const uint32_t np = (lane < NSEG && fv.y == lid) ? fv.x >> 16 : 0u;
            uint32_t inc = np;
#pragma unroll
            for (int o = 1; o < 16; o <<= 1) { const uint32_t v = __shfl_up_sync(~0u, inc, o); if (lane >= o) inc += v; }
            const uint32_t first = np ? inc - np : 0xffffffffu;
            const uint32_t total = __shfl_sync(~0u, inc, NSEG - 1);
            const uint32_t delta = (warp * NSEG + lane) * RP + (fv.x & 0xffff) - first;
            const uint32_t curb = sb + SM_CUR - (tag + node0) * 4;
#pragma unroll 1
            for (uint32_t r0 = 0; r0 == 0 || r0 * 32 < total; r0 += NRD) {
                const uint4* ad[NRD];
#pragma unroll
                for (int i = 0; i < NRD; i++) {
                    const uint32_t r = r0 + i;
                    const uint32_t starts = __reduce_or_sync(~0u, (first >> 5) == r ? 1u << (first & 31) : 0u);
                    const uint32_t seg = __popc(__ballot_sync(~0u, (first >> 5) < r)) + __popc(starts & (0xffffffffu >> (31 - lane))) - 1;
                    ad[i] = sc->rec + (__shfl_sync(~0u, delta, seg) + min(r * 32 + lane, total - 1));
                }
                if (r0 == 0) {
                    bar_sync(BAR_FREE, NTE);
                    __nanosleep(SENTMODE);
                    STAMP(9);
                    if (total == 0) break;
                }
                uint4 q[NRD];
                bool wait;
                do {
                    uint32_t bad = 0;
#pragma unroll
                    for (int i = 0; i < NRD; i++) q[i] = ld_relaxed2x64(ad[i]);
#pragma unroll
                    for (int i = 0; i < NRD; i++) bad |= (q[i].y ^ tag) | (q[i].w ^ tag);
                    wait = __any_sync(~0u, bad >> 16);
                } while (wait && ++spin < SPIN_LIMIT);
                STAMP(21);
                if (wait) break;
#pragma unroll
                for (int i = 0; i < NRD; i++) {
                    const bool ok = (r0 + i) * 32 + lane < total;
                    q[i].y = atoms_add(ok ? curb + q[i].y * 4 : sb + SM_CUR + (384 + lane) * 4, 4);
                    q[i].w = atoms_add(ok ? curb + q[i].w * 4 : sb + SM_CUR + (384 + lane) * 4, 4);
                }
#pragma unroll
                for (int i = 0; i < NRD; i++) {
                    sts_u32(min(q[i].y, sb + SM_HIST + lane * 4), q[i].x);
                    sts_u32(min(q[i].w, sb + SM_HIST + lane * 4), q[i].z);
                }
            }
            STAMP(10);
            if (warp < 6) {
                bar_sync(BAR_C, NWC * 32);
                uint32_t dg[2], qq[2];
#pragma unroll
                for (int k = 0; k < 2; k++) {
                    dg[k] = tid + 192 * k < NPB ? (sCur[tid + 192 * k] - (sb + SM_SLOT)) / 4 - (tid + 192 * k) * CAPD : 0u;
                    if (dg[k] > CAPD) { sMisc[0] = 1; dg[k] = CAPD; }
                }
#pragma unroll
                for (int k = 0; k < 2; k++) qq[k] = atomicAdd(&sDh[dg[k]], 1u);
                bar_sync(BAR_E, 192);
                const uint2 c2 = *reinterpret_cast<const uint2*>(sDh + 62 - 2 * lane);
                uint32_t inc2 = c2.x + c2.y;
#pragma unroll
                for (int o = 1; o < 32; o <<= 1) { const uint32_t v = __shfl_up_sync(~0u, inc2, o); if (lane >= o) inc2 += v; }
#pragma unroll
                for (int k = 0; k < 2; k++) {
                    const uint32_t pk = __shfl_sync(~0u, (inc2 - c2.x) | ((inc2 - c2.x - c2.y) << 16), (63 - dg[k]) >> 1);
                    sOrd[((dg[k] & 1) ? pk >> 16 : pk & 0xffff) + qq[k]] = (tid + 192 * k) | (dg[k] << 16);
                }
            } else {
                bar_arrive(BAR_C, NWC * 32);
            }
            STAMP(11);
        }
    } else {
        const int aw = warp - NWE, at = tid - NTE;
        const uint4* hg = reinterpret_cast<const uint4*>(h + (size_t)node0 * 64) + at;
        const uint32_t hs = sb + SM_H + ((at ^ ((at >> 3) & 7)) << 4);
        auto load_tile = [&](int tile) {
#pragma unroll
            for (int k = 0; k < 4; k++)
                if (tile * 512 + k * 128 + at < nvalid * 8)
                    asm volatile("cp.async.cg.shared.global [%0], [%1], 16;" :: "r"(hs + tile * 8192 + k * 2048), "l"(hg + tile * 512 + k * 128));
            asm volatile("cp.async.commit_group;" ::: "memory");
        };
        uint32_t op[3][3];
        {
#pragma unroll
            for (int j = 0; j < 3; j++) {
                const unsigned short* pg = reinterpret_cast<const unsigned short*>(pos) + (size_t)(node0 + min(at + 128 * j, nvalid - 1)) * 3;
                op[j][0] = __ldg(pg); op[j][1] = __ldg(pg + 1); op[j][2] = __ldg(pg + 2);
            }
            if (at < 2) sTag[at] = NN;
            int ch = lane & 7;
            if (aw == 1) ch = ((ch & 3) << 1) | (ch >> 2);
            const int rr = lane >> 3;
            uint32_t* sw = reinterpret_cast<uint32_t*>(smem + (aw == 3 ? SM_W2 : SM_W + ((aw + 2) % 3) * 8192)) + rr * 32 + (ch & 3);
#pragma unroll
            for (int j = 0; j < 16; j++) {
                const int4 w = j < RND ? vd[j] : wv[j < RND ? 0 : j - RND];
                const int x = (ch & 4) ^ (aw == 3 ? ((((j >> 1) & 3) << 1) | (rr & 1)) : (rr | ((j & 1) << 2)));
                sw[j * 128 + ((x ^ 0) << 2)] = half_bf16x2(w.x);
                sw[j * 128 + ((x ^ 1) << 2)] = half_bf16x2(w.y);
                sw[j * 128 + ((x ^ 2) << 2)] = half_bf16x2(w.z);
                sw[j * 128 + ((x ^ 3) << 2)] = half_bf16x2(w.w);
            }
            fence_async_smem();
        }
        STAMPW(NWE + 2, 20);
        bar_sync(BAR_GO, NT);
#pragma unroll
        for (int k = 0; k < HWIN; k++) load_tile(k);
#pragma unroll
        for (int j = 0; j < 3; j++) {
            const int n = at + 128 * j;
            const uint2 v = make_uint2(op[j][0] | (op[j][1] << 16), op[j][2]);
            *reinterpret_cast<uint2*>(smem + SM_POS + n * 8) = v;
            if (n < nvalid)
#pragma unroll
                for (int k = 0; k < PQ; k++) sc->pos[(node0 + n) * PQ + k] = v;
        }
        if (b == 0 && at < 8) sc->B[NN * BQ + at] = make_uint4(0xf149f149u, 0xf149f149u, 0xf149f149u, 0xf149f149u);
        if (b == 0 && at >= 8 && at < 12) sc->pos[NN * PQ + at - 8] = make_uint2(0, 0);

        const uint64_t dw = wg_desc(sb + SM_W);
        auto piece = [&](const float (&o)[32], int half, int up) {
            return make_uint4(pack_bf16(o[16 * half + 2 * up], o[16 * half + 2 * up + 1]), pack_bf16(o[16 * half + 4 + 2 * up], o[16 * half + 5 + 2 * up]),
                              pack_bf16(o[16 * half + 8 + 2 * up], o[16 * half + 9 + 2 * up]), pack_bf16(o[16 * half + 12 + 2 * up], o[16 * half + 13 + 2 * up]));
        };
        auto issue = [&](float (&o)[32], int tile, int mat) {
            const uint64_t da = wg_desc(sb + SM_H + tile * 8192);
            asm volatile("wgmma.fence.sync.aligned;" ::: "memory");
#pragma unroll
            for (int kk = 0; kk < 4; kk++) wgmma64(o, da + 2 * kk, dw + mat * 512 + 128 * kk, kk);
            asm volatile("wgmma.commit_group.sync.aligned;" ::: "memory");
        };
#define WG_WAIT(n, o) do { asm volatile("wgmma.wait_group.sync.aligned " #n ";" ::: "memory"); \
        _Pragma("unroll") for (int i_ = 0; i_ < 32; i_++) asm volatile("" : "+f"(o[i_]) :: "memory"); } while (0)
        auto store_s = [&](const float (&o)[32], int base, int tile) {
#pragma unroll
            for (int i = 0; i < 4; i++) *srow(smem + base, tile * 64 + aw * 16 + g + 8 * (i >> 1), t, i & 1) = piece(o, i & 1, i >> 1);
        };
        float o1[32], o2[32];
        auto stage_b = [&](const float (&o)[32], int slot) {
#pragma unroll
            for (int i = 0; i < 4; i++)
                reinterpret_cast<uint4*>(smem + SM_U + (slot * 64 + aw * 16 + g + 8 * (i >> 1)) * 128)[t + 4 * (i & 1)] = piece(o, i & 1, i >> 1);
        };
#pragma unroll 1
        for (int k0 = 0; k0 < 6; k0 += 3) {
#pragma unroll
            for (int k = 0; k < 3; k++) {
                asm volatile("cp.async.wait_group %0;" :: "n"(HWIN - 1) : "memory");
                load_tile(k0 + k + HWIN);
            }
            fence_async_smem();
            bar_sync(BAR_G, 128);
            STAMPW(NWE, 5 + k0 / 3);
            issue(o1, k0, 0);
            issue(o2, k0 + 1, 0);
            if (k0 == 0) bar_sync(BAR_PRIO, 160);
            else {
                if (at == 0) asm volatile("cp.async.bulk.wait_group.read 0;" ::: "memory");
                bar_sync(BAR_G, 128);
            }
            WG_WAIT(1, o1);
            stage_b(o1, 0);
            issue(o1, k0 + 2, 0);
            WG_WAIT(1, o2);
            stage_b(o2, 1);
            WG_WAIT(0, o1);
            stage_b(o1, 2);
            fence_async_smem();
            bar_sync(BAR_G, 128);
            if (at == 0) bulk_s2g(sc->B + (size_t)(node0 + k0 * 64) * 8, sb + SM_U, min(192, nvalid - k0 * 64) * 128);
        }
        STAMPW(NWE, 7);
        {
            issue(o2, 3, 1);
            issue(o1, 3, 2);
            WG_WAIT(1, o2);
            store_s(o2, SM_U, 3);
            issue(o2, 0, 1);
            WG_WAIT(1, o1);
            store_s(o1, SM_H, 3);
            issue(o1, 0, 2);
            if (at == 0) bulk_wait();
            __syncwarp();
            bar_arrive(BAR_B, 160);
            bar_sync(BAR_G, 128);
#pragma unroll
            for (int k = 0; k < 3; k++) {
                WG_WAIT(1, o2);
                store_s(o2, SM_U, k);
                issue(o2, k < 2 ? k + 1 : 5, 1);
                WG_WAIT(1, o1);
                store_s(o1, SM_H, k);
                issue(o1, k < 2 ? k + 1 : 4, k < 2 ? 2 : 1);
            }
            WG_WAIT(1, o2);
            uint4 uk[4];
#pragma unroll
            for (int i = 0; i < 4; i++) uk[i] = piece(o2, i & 1, i >> 1);
            issue(o2, 5, 2);
            WG_WAIT(1, o1);
            bar_sync(BAR_G, 128);
            store_s(o1, SM_U, 4);
            issue(o1, 4, 2);
            WG_WAIT(1, o2);
            store_s(o2, SM_H, 5);
            WG_WAIT(0, o1);
            store_s(o1, SM_H, 4);
            bar_sync(BAR_G, 128);
#pragma unroll
            for (int i = 0; i < 4; i++) *srow(smem + SM_U, 5 * 64 + aw * 16 + g + 8 * (i >> 1), t, i & 1) = uk[i];
        }
        if (aw == 3) {
            const unsigned short* we = reinterpret_cast<const unsigned short*>(w_e) + (t < 3 ? 128 : 129) * 64;
            const uint32_t* wx = reinterpret_cast<const uint32_t*>(w_x);
            uint32_t c[12];
#pragma unroll
            for (int j = 0; j < 4; j++) {
                const int fc = 8 * (g >> 1) + 4 * (j & 1) + (g & 1) + 32 * (j >> 1);
                const uint32_t w = (uint32_t)__ldg(we + fc) | ((uint32_t)__ldg(we + fc + 2) << 16);
                c[j] = hmul2_bf16(w, t < 3 ? 0x3f003f00u : 0xbf00bf00u);
                const uint32_t x = __ldg(wx + 4 * t + 2 * (j & 1) + (g & 1) + 16 * (j >> 1));
                c[4 + 2 * j] = (g & 2) ? 0u : x;
                c[5 + 2 * j] = (g & 2) ? x : 0u;
            }
#pragma unroll
            for (int j = 0; j < 3; j++)
                reinterpret_cast<uint4*>(smem + SM_CONST)[j * 32 + lane] = make_uint4(c[4 * j], c[4 * j + 1], c[4 * j + 2], c[4 * j + 3]);
            const uint32_t id = ((2 * t == g) ? 0x3f80u : 0u) | ((2 * t + 1 == g) ? 0x3f800000u : 0u);
            reinterpret_cast<uint4*>(smem + SM_CONST)[96 + lane] = make_uint4(id, id, 128u, 8u);
            reinterpret_cast<uint4*>(smem + SM_CONST)[128 + lane] =
                make_uint4(t < 3 ? 0xffffffffu : 0u, (t & 1) ? 0x3244u : 0x1044u, (t & 1) ? 0x1044u : 0x3244u, 0u);
            reinterpret_cast<ulonglong2*>(smem + SM_CONST)[160 + lane] =
                make_ulonglong2(reinterpret_cast<unsigned long long>(sc->B) + t * 32, reinterpret_cast<unsigned long long>(sc->pos) + t * 2);
        }
        STAMPW(NWE, 8);
    }

    __syncthreads();
    STAMP(12);
    uint32_t wda[4], wxr[4][2], ident, ident2, sqmask, selown, seloth;
    {
        const uint4* cp = reinterpret_cast<const uint4*>(smem + SM_CONST) + lane;
        const uint4 c0 = cp[0], c1 = cp[32], c2 = cp[64], c3 = cp[96], c4 = cp[128];
        wda[0] = c0.x; wda[1] = c0.y; wda[2] = c0.z; wda[3] = c0.w;
        wxr[0][0] = c1.x; wxr[0][1] = c1.y; wxr[1][0] = c1.z; wxr[1][1] = c1.w;
        wxr[2][0] = c2.x; wxr[2][1] = c2.y; wxr[3][0] = c2.z; wxr[3][1] = c2.w;
        ident = c3.x; ident2 = c3.y; sqmask = c4.x; selown = c4.y; seloth = c4.z;
    }
    if (sMisc[0]) {
        slow_path(sc, smem, h, pos, eattr, src, dst, w_e, w_x, out, node0, nvalid, ident);
        return;
    }

    const ulonglong2 bases = reinterpret_cast<const ulonglong2*>(smem + SM_CONST)[160 + lane];
    const unsigned long long bbase = bases.x, pbase = bases.y;
    uint4 a0, a1, b0, b1;
    uint32_t psA, psB, e2;
    uint32_t og[3];
#pragma unroll
    for (int k = 0; k < 3; k++) {
        const int gi = k == 0 ? warp : (k + 1) * NW - 1 - warp;
        const uint32_t o = sOrd[gi * 8 + g];
        const uint32_t len = max(sOrd[gi * 8] >> 16, 1u);
        uint32_t* sl = sSlot + (o & 0xffff) * CAPD;
#pragma unroll 1
        for (uint32_t r = (o >> 16) + t; r < ((len + 1) & ~1u); r += 4) sl[r] = NN;
        og[k] = (o & 0xffff) | (len << 16);
    }
    __syncwarp();
    auto gather = [&](uint4& lo, uint4& hi, uint32_t& ps, uint32_t sw) {
        asm volatile("{\n\t.reg .u32 s;\n\t.reg .u64 a, c;\n\t"
                     "and.b32 s, %9, " XMASK ";\n\t"
                     "mad.wide.u32 a, s, %12, %10;\n\t"
                     "mad.wide.u32 c, s, " XPM ", %11;\n\t"
                     "ld.global" BH1 ".v4.u32 {%0,%1,%2,%3}, [a];\n\t"
                     "ld.global" BH2 ".v4.u32 {%4,%5,%6,%7}, [a+16];\n\t"
                     "ld.global.u16 %8, [c];\n\t}"
                     : "=r"(lo.x), "=r"(lo.y), "=r"(lo.z), "=r"(lo.w), "=r"(hi.x), "=r"(hi.y), "=r"(hi.z), "=r"(hi.w), "=r"(ps)
                     : "r"(sw), "l"(bbase), "l"(pbase), "n"(BQ * 16), "n"(PQ * 8));
    };
    auto lds64 = [&](uint32_t addr) -> uint2 {
        uint2 v;
        asm volatile("ld.shared.v2.u32 {%0,%1}, [%2];" : "=r"(v.x), "=r"(v.y) : "r"(addr) : "memory");
        return v;
    };
    uint32_t sp = sb + SM_SLOT + (og[0] & 0xffff) * (CAPD * 4);
    STAMP(13);
    {
        const uint2 sw = lds64(sp);
        gather(a0, a1, psA, sw.x);
        gather(b0, b1, psB, sw.y);
        e2 = __byte_perm(sw.x, sw.y, 0x7632);
    }
#pragma unroll 1
    for (int k = 0; k < 3; k++) {
        const int n = og[0] & 0xffff, len = og[0] >> 16;
        const uint32_t spn = k < 2 ? sb + SM_SLOT + (og[1] & 0xffff) * (CAPD * 4) : sb + SM_TAG;
        og[0] = og[1];
        og[1] = og[2];
        float ci[4][4], acc[4][4];
        {
            uint32_t ar[8];
            load_srow(ar, smem + SM_H, n, t);
#pragma unroll
            for (int j = 0; j < 4; j++) {
                ci[j][0] = bf_lo(ar[2 * j]); ci[j][1] = bf_hi(ar[2 * j]);
                ci[j][2] = bf_lo(ar[2 * j + 1]); ci[j][3] = bf_hi(ar[2 * j + 1]);
                acc[j][0] = acc[j][1] = acc[j][2] = acc[j][3] = 0.f;
            }
        }
        const uint32_t pd2 = lds_u16(sb + SM_POS + n * 8 + 2 * t) * 0x10001u;
        float px = 0.f;
        auto step = [&](auto both) {
            constexpr bool BOTH = decltype(both)::value;
            const uint2 sw = lds64(sp);
            const uint32_t ps2 = __byte_perm(psA, psB, 0x5410) | (e2 & ~sqmask);
            const uint32_t df = hsub2_bf16(pd2, ps2);
            const uint32_t x2 = hmul2_bf16(df, (df & sqmask) | (0x3f803f80u & ~sqmask));
            const uint32_t ra[8] = {a0.x, a0.y, a0.z, a0.w, a1.x, a1.y, a1.z, a1.w};
            const uint32_t rb[8] = {b0.x, b0.y, b0.z, b0.w, b1.x, b1.y, b1.z, b1.w};
            float da[4][4], db[4][4];
#pragma unroll
            for (int j = 0; j < 4; j++) {
                mma8(da[j], ra[2 * j], ra[2 * j + 1], ident, ci[j]);
                if (BOTH) mma8(db[j], rb[2 * j], rb[2 * j + 1], ident, ci[j]);
            }
            gather(a0, a1, psA, sw.x);
            gather(b0, b1, psB, sw.y);
            e2 = __byte_perm(sw.x, sw.y, 0x7632);
#pragma unroll
            for (int j = 0; j < 4; j++) {
                mma8_acc(da[j], x2 & 0xffffu, x2 << 16, wda[j]);
                if (BOTH) mma8_acc(db[j], x2 >> 16, x2 & 0xffff0000u, wda[j]);
            }
            float cs[4] = {0.f, 0.f, 0.f, 0.f};
#pragma unroll
            for (int j = 0; j < 4; j++) {
                const uint32_t m0 = pack_bf16(silu_half(da[j][0]), silu_half(da[j][1]));
                const uint32_t m1 = pack_bf16(silu_half(da[j][2]), silu_half(da[j][3]));
                if (BOTH) {
                    const uint32_t m2 = pack_bf16(silu_half(db[j][0]), silu_half(db[j][1]));
                    const uint32_t m3 = pack_bf16(silu_half(db[j][2]), silu_half(db[j][3]));
                    mma16_acc(acc[j], m0, m1, m2, m3, ident, ident2);
                    mma16_acc(cs, m0, m1, m2, m3, wxr[j][0], wxr[j][1]);
                } else {
                    mma8_acc(acc[j], m0, m1, ident);
                    mma8_acc(cs, m0, m1, wxr[j][0]);
                }
            }
            const float own = cs[0] + cs[3];
            const float oth = __shfl_xor_sync(~0u, own, 1);
            px = fmaf(__uint_as_float(__byte_perm(df, 0, selown)), own, px);
            px = fmaf(__uint_as_float(__byte_perm(df, 0, seloth)), oth, px);
        };
        const uint32_t spe = sp + ((len - 1) >> 1) * 8;
#pragma unroll 1
        while (sp != spe) {
            sp += 8;
            step(std::true_type());
        }
        sp = spn;
        if (len & 1) step(std::false_type());
        else step(std::true_type());
        {
            if (t < 3 && n < nvalid) out[(size_t)NN * 64 + (node0 + n) * 3 + t] = __float2bfloat16(bf_lo(pd2) + px);
            uint32_t m[8];
#pragma unroll
            for (int j = 0; j < 4; j++) { m[2 * j] = pack_bf16(acc[j][0], acc[j][1]); m[2 * j + 1] = pack_bf16(acc[j][2], acc[j][3]); }
            node_update(smem, m, n, nvalid, node0, ident, h, out);
        }
    }
}

}

extern "C" void kernel_launch(void* const* d_in, const int* in_sizes, int n_in, void* d_out, int out_size) {
    (void)in_sizes; (void)n_in; (void)out_size;
    static Scratch* sc = nullptr;
    if (!sc) {
        cudaFuncSetAttribute(egnn_kernel, cudaFuncAttributeMaxDynamicSharedMemorySize, SM_TOTAL + DBG_SMEM);
        cudaGetSymbolAddress(reinterpret_cast<void**>(&sc), g_scratch);
    }
    egnn_kernel<<<NB, NT, SM_TOTAL + DBG_SMEM>>>(
        (const __nv_bfloat16*)d_in[0], (const __nv_bfloat16*)d_in[1], (const __nv_bfloat16*)d_in[2],
        (const int*)d_in[3], (const int*)d_in[4], (const __nv_bfloat16*)d_in[5], (const __nv_bfloat16*)d_in[6],
        (const __nv_bfloat16*)d_in[7], (__nv_bfloat16*)d_out, sc);
}
```

```cpp
#include <cuda_runtime.h>
#include <cuda_bf16.h>
#include <stdint.h>
#include <type_traits>

namespace {

constexpr int NN = 50000;
constexpr int EE = 800000;
constexpr int NB = 132;
constexpr int NPB = 379;
constexpr int EPB = 6064;
constexpr int NWE = 12;
constexpr int NWC = 11;
constexpr int NTE = NWE * 32;
constexpr int NW = NWE + 4;
constexpr int NT = NW * 32;
constexpr int RND = (EPB / 4 + NTE - 1) / NTE;
constexpr int RU = 2160;
constexpr int NG = 48;
constexpr int CAPD = 50;
constexpr int NSEG = 12;
constexpr int NRD = 7;
constexpr int HWIN = 4;
#define V_DEFER 0
#define K_AB 0
#define K_LD 0
#define K_PJ 0x3210
#define K_CS 0
#define K_BF 0
#define K_AC 0
#define K_SUM 0
constexpr unsigned SPIN_LIMIT = 1u << 24;

constexpr int SM_W2 = 0;
constexpr int SM_H = SM_W2 + 8192;
constexpr int SM_U = SM_H + 49152;
constexpr int SM_W = SM_U + 24576;
constexpr int SM_SLOT = SM_U + 49152;
constexpr int SM_SRC = SM_U;
constexpr int SM_IDX = SM_SLOT + 6 * NTE * 16;
constexpr int SM_EA = SM_SLOT + 52224;
constexpr int SM_HIST = SM_SLOT + 384 * CAPD * 4;
constexpr int SM_DH = SM_HIST + 160 * 4;
constexpr int SM_MISC = SM_DH + 64 * 4;
constexpr int SM_CUR = SM_MISC + 64;
constexpr int SM_ORD = SM_CUR + 416 * 4;
constexpr int SM_POS = SM_ORD + 384 * 4;
constexpr int SM_CONST = SM_POS + 384 * 8;
constexpr int SM_TAG = SM_CONST + 3072;
constexpr int SM_TOTAL = SM_TAG + 64;
static_assert(RU >= EPB / 3 + 1 + NB && RU <= 6 * NTE && 6 * NTE >= RND * NTE * 4 / 3 + 160 && SM_IDX + 6 * NTE * 4 <= SM_EA && SM_EA + RND * NTE * 8 <= SM_HIST &&
              RND * NTE * 16 <= SM_W - SM_SRC && (RND - 1) * NTE * 4 <= EE - (NB - 1) * EPB, "edge rounds");
static_assert(NG == 3 * NW && NWE % 4 == 0 && CAPD % 2 == 0 && CAPD <= 62 && (SM_CUR - SM_HIST) == 60 * 16 && SM_W % 1024 == 0, "work split");
static_assert(NN - (NB - 1) * NPB > 320 && SM_TAG % 8 == 0 && SM_TOTAL <= 232448 && NWC * NSEG == NB && NTE == 384, "layout");

struct Scratch {
    uint4 B[NB * 384 * 8];
    uint4 rec[NB * RU];
    uint2 pos[NB * 384];
    uint2 flag[NB * 160];
    uint32_t sync[32];
    float acc[NB * 384 * 68];
};
__device__ __align__(1024) Scratch g_scratch;

#define STAMPW(w, i)
#define DBG_SMEM 0
#define STAMP(i) STAMPW(0, i)

__device__ __forceinline__ uint32_t smem_u32(const void* p) { return (uint32_t)__cvta_generic_to_shared(p); }

__device__ __forceinline__ void mma16_acc(float (&d)[4], uint32_t a0, uint32_t a1, uint32_t a2, uint32_t a3,
                                          uint32_t b0, uint32_t b1) {
    asm("mma.sync.aligned.m16n8k16.row.col.f32.bf16.bf16.f32 {%0,%1,%2,%3}, {%4,%5,%6,%7}, {%8,%9}, {%0,%1,%2,%3};"
        : "+f"(d[0]), "+f"(d[1]), "+f"(d[2]), "+f"(d[3])
        : "r"(a0), "r"(a1), "r"(a2), "r"(a3), "r"(b0), "r"(b1));
}
__device__ __forceinline__ void mma8_acc(float (&d)[4], uint32_t a0, uint32_t a1, uint32_t b0) {
    asm("mma.sync.aligned.m16n8k8.row.col.f32.bf16.bf16.f32 {%0,%1,%2,%3}, {%4,%5}, {%6}, {%0,%1,%2,%3};"
        : "+f"(d[0]), "+f"(d[1]), "+f"(d[2]), "+f"(d[3])
        : "r"(a0), "r"(a1), "r"(b0));
}
__device__ __forceinline__ void mma8(float (&d)[4], uint32_t a0, uint32_t a1, uint32_t b0, const float (&c)[4]) {
    asm("mma.sync.aligned.m16n8k8.row.col.f32.bf16.bf16.f32 {%0,%1,%2,%3}, {%4,%5}, {%6}, {%7,%8,%9,%10};"
        : "=f"(d[0]), "=f"(d[1]), "=f"(d[2]), "=f"(d[3])
        : "r"(a0), "r"(a1), "r"(b0), "f"(c[0]), "f"(c[1]), "f"(c[2]), "f"(c[3]));
}
__device__ __forceinline__ void wgmma64(float (&d)[32], uint64_t da, uint64_t db, int acc) {
    asm volatile("{\n\t.reg .pred p;\n\tsetp.ne.b32 p, %34, 0;\n\t"
                 "wgmma.mma_async.sync.aligned.m64n64k16.f32.bf16.bf16 "
                 "{%0,%1,%2,%3,%4,%5,%6,%7,%8,%9,%10,%11,%12,%13,%14,%15,%16,%17,%18,%19,%20,%21,%22,%23,%24,%25,%26,%27,%28,%29,%30,%31}, "
                 "%32, %33, p, 1, 1, 0, 1;\n\t}"
                 : "+f"(d[0]), "+f"(d[1]), "+f"(d[2]), "+f"(d[3]), "+f"(d[4]), "+f"(d[5]), "+f"(d[6]), "+f"(d[7]),
                   "+f"(d[8]), "+f"(d[9]), "+f"(d[10]), "+f"(d[11]), "+f"(d[12]), "+f"(d[13]), "+f"(d[14]), "+f"(d[15]),
                   "+f"(d[16]), "+f"(d[17]), "+f"(d[18]), "+f"(d[19]), "+f"(d[20]), "+f"(d[21]), "+f"(d[22]), "+f"(d[23]),
                   "+f"(d[24]), "+f"(d[25]), "+f"(d[26]), "+f"(d[27]), "+f"(d[28]), "+f"(d[29]), "+f"(d[30]), "+f"(d[31])
                 : "l"(da), "l"(db), "r"(acc));
}
__device__ __forceinline__ uint64_t wg_desc(uint32_t addr) {
    return (uint64_t)((addr & 0x3ffff) >> 4) | ((uint64_t)1 << 16) | ((uint64_t)64 << 32) | ((uint64_t)1 << 62);
}
__device__ __forceinline__ void ldsm4t(uint32_t (&r)[4], uint32_t addr) {
    asm volatile("ldmatrix.sync.aligned.m8n8.x4.trans.shared.b16 {%0,%1,%2,%3}, [%4];"
                 : "=r"(r[0]), "=r"(r[1]), "=r"(r[2]), "=r"(r[3]) : "r"(addr));
}
__device__ __forceinline__ uint32_t movm(uint32_t a) {
    uint32_t d;
    asm("movmatrix.sync.aligned.m8n8.trans.b16 %0, %1;" : "=r"(d) : "r"(a));
    return d;
}
__device__ __forceinline__ uint32_t pack_bf16(float lo, float hi) {
    uint32_t r;
    asm("cvt.rn.bf16x2.f32 %0, %1, %2;" : "=r"(r) : "f"(hi), "f"(lo));
    return r;
}
__device__ __forceinline__ float tanh_fast(float x) {
    float y;
    asm("tanh.approx.f32 %0, %1;" : "=f"(y) : "f"(x));
    return y;
}
__device__ __forceinline__ float silu_half(float hx) { return fmaf(hx, tanh_fast(hx), hx); }
__device__ __forceinline__ uint32_t hadd2_bf16(uint32_t a, uint32_t b) {
    uint32_t r;
    asm("add.rn.bf16x2 %0, %1, %2;" : "=r"(r) : "r"(a), "r"(b));
    return r;
}
__device__ __forceinline__ uint32_t hsub2_bf16(uint32_t a, uint32_t b) {
    uint32_t r;
    asm("sub.rn.bf16x2 %0, %1, %2;" : "=r"(r) : "r"(a), "r"(b));
    return r;
}
__device__ __forceinline__ uint32_t hmul2_bf16(uint32_t a, uint32_t b) {
    uint32_t r;
    asm("mul.rn.bf16x2 %0, %1, %2;" : "=r"(r) : "r"(a), "r"(b));
    return r;
}
__device__ __forceinline__ float bf_lo(uint32_t v) { return __uint_as_float(v << 16); }
__device__ __forceinline__ float bf_hi(uint32_t v) { return __uint_as_float(v & 0xffff0000u); }
__device__ __forceinline__ uint32_t half_bf16x2(uint32_t v) { return hmul2_bf16(v, 0x3f003f00u); }
template <typename T> __device__ __forceinline__ T opaque(T v) { asm volatile("" : "+r"(v)); return v; }

__device__ __forceinline__ uint32_t ld_relaxed(const uint32_t* p) {
    uint32_t v;
    asm volatile("ld.relaxed.gpu.global.u32 %0, [%1];" : "=r"(v) : "l"(p) : "memory");
    return v;
}
__device__ __forceinline__ uint2 ld_relaxed64(const uint2* p) {
    unsigned long long v;
    asm volatile("ld.relaxed.gpu.global.u64 %0, [%1];" : "=l"(v) : "l"(p) : "memory");
    return make_uint2((uint32_t)v, (uint32_t)(v >> 32));
}
__device__ __forceinline__ uint4 ld_relaxed128(const uint4* p) {
    uint4 v;
    asm volatile("ld.relaxed.gpu.global.v4.u32 {%0,%1,%2,%3}, [%4];" : "=r"(v.x), "=r"(v.y), "=r"(v.z), "=r"(v.w) : "l"(p) : "memory");
    return v;
}
__device__ __forceinline__ uint32_t atoms_add(uint32_t addr, uint32_t v) {
    uint32_t r;
    asm volatile("atom.shared.add.u32 %0, [%1], %2;" : "=r"(r) : "r"(addr), "r"(v) : "memory");
    return r;
}
__device__ __forceinline__ uint32_t lds_u32(uint32_t addr) {
    uint32_t v;
    asm volatile("ld.shared.u32 %0, [%1];" : "=r"(v) : "r"(addr) : "memory");
    return v;
}
__device__ __forceinline__ void sts_u32(uint32_t addr, uint32_t v) { asm volatile("st.shared.u32 [%0], %1;" :: "r"(addr), "r"(v) : "memory"); }
__device__ __forceinline__ void st_relaxed64(uint2* p, uint32_t lo, uint32_t hi) {
    asm volatile("st.relaxed.gpu.global.u64 [%0], %1;" :: "l"(p), "l"((unsigned long long)lo | ((unsigned long long)hi << 32)) : "memory");
}
__device__ __forceinline__ void st_relaxed(uint32_t* p, uint32_t v) {
    asm volatile("st.relaxed.gpu.global.u32 [%0], %1;" :: "l"(p), "r"(v) : "memory");
}
__device__ __forceinline__ void fence_gpu() { asm volatile("fence.acq_rel.gpu;" ::: "memory"); }
__device__ __forceinline__ void fence_async_smem() { asm volatile("fence.proxy.async.shared::cta;" ::: "memory"); }
__device__ __forceinline__ void bar_sync(int id, int n) { asm volatile("bar.sync %0, %1;" :: "r"(id), "r"(n) : "memory"); }
__device__ __forceinline__ void bar_arrive(int id, int n) { asm volatile("bar.arrive %0, %1;" :: "r"(id), "r"(n) : "memory"); }

__device__ __forceinline__ void bulk_s2g(void* dst, uint32_t src, uint32_t bytes) {
    asm volatile("cp.async.bulk.global.shared::cta.bulk_group [%0], [%1], %2;" :: "l"(dst), "r"(src), "r"(bytes) : "memory");
    asm volatile("cp.async.bulk.commit_group;" ::: "memory");
}
__device__ __forceinline__ void bulk_wait() { asm volatile("cp.async.bulk.wait_group 0;" ::: "memory"); }

__device__ __forceinline__ uint32_t lds_u16(uint32_t addr) {
    uint32_t v;
    asm volatile("ld.shared.u16 %0, [%1];" : "=r"(v) : "r"(addr));
    return v;
}
__device__ __forceinline__ int4 ldg_stream4(const void* p) {
    int4 v;
    asm volatile("ld.global.L1::no_allocate.v4.u32 {%0,%1,%2,%3}, [%4];" : "=r"(v.x), "=r"(v.y), "=r"(v.z), "=r"(v.w) : "l"(p));
    return v;
}
__device__ __forceinline__ uint2 ldg_stream2(const void* p) {
    uint2 v;
    asm volatile("ld.global.L1::no_allocate.v2.u32 {%0,%1}, [%2];" : "=r"(v.x), "=r"(v.y) : "l"(p));
    return v;
}

__device__ __forceinline__ uint4* srow(unsigned char* tile, int row, int t, int half) {
    return reinterpret_cast<uint4*>(tile + row * 128) + (t + (((row ^ half) & 1) << 2));
}
__device__ __forceinline__ void load_srow(uint32_t (&r)[8], unsigned char* tile, int row, int t) {
    const uint4 u = *srow(tile, row, t, 0), v = *srow(tile, row, t, 1);
    r[0] = u.x; r[1] = u.y; r[2] = u.z; r[3] = u.w; r[4] = v.x; r[5] = v.y; r[6] = v.z; r[7] = v.w;
}

__device__ __forceinline__ void node_update(unsigned char* smem, uint32_t (&m)[8], int n, int nvalid, int node0,
                                            uint32_t ident, const __nv_bfloat16* __restrict__ h,
                                            __nv_bfloat16* __restrict__ out) {
    const int lane = threadIdx.x & 31, t = lane & 3, i = lane & 7;
    const uint4* hp = reinterpret_cast<const uint4*>(h + (size_t)(node0 + min(n, nvalid - 1)) * 64) + t;
    const uint4 h0 = __ldg(hp), h1 = __ldg(hp + 4);
    const uint32_t wl = smem_u32(smem) + SM_W2 + (8 * (i >> 1) + 2 * (lane >> 4) + (i & 1)) * 128 + (((((lane >> 3) & 1) ^ i)) << 4);
    uint32_t ur[8];
    load_srow(ur, smem + SM_U, n, t);
    float o[4][4];
#pragma unroll
    for (int mt = 0; mt < 4; mt++) {
        o[mt][0] = o[mt][1] = o[mt][2] = o[mt][3] = 0.f;
        mma16_acc(o[mt], ident, 0u, 0u, ident, ur[2 * mt], ur[2 * mt + 1]);
    }
#pragma unroll
    for (int kk = 0; kk < 4; kk++)
#pragma unroll
        for (int mt = 0; mt < 4; mt++) {
            uint32_t w[4];
            ldsm4t(w, (wl ^ (mt << 5)) + (4 * (kk & 1) + 32 * (kk >> 1)) * 128);
            mma16_acc(o[mt], w[0], w[1], w[2], w[3], m[2 * kk], m[2 * kk + 1]);
        }
    const uint32_t hr[8] = {h0.x, h0.y, h0.z, h0.w, h1.x, h1.y, h1.z, h1.w};
#pragma unroll
    for (int j = 0; j < 4; j++) {
        m[2 * j] = hadd2_bf16(hr[2 * j], movm(pack_bf16(silu_half(o[j][0]), silu_half(o[j][1]))));
        m[2 * j + 1] = hadd2_bf16(hr[2 * j + 1], movm(pack_bf16(silu_half(o[j][2]), silu_half(o[j][3]))));
    }
    if (n < nvalid) {
        uint4* p = reinterpret_cast<uint4*>(out + (size_t)(node0 + n) * 64) + t;
        p[0] = make_uint4(m[0], m[1], m[2], m[3]);
        p[4] = make_uint4(m[4], m[5], m[6], m[7]);
    }
}

__device__ __noinline__ void slow_path(Scratch* sc, unsigned char* smem, const __nv_bfloat16* __restrict__ h,
                                       const __nv_bfloat16* __restrict__ pos,
                                       const __nv_bfloat16* __restrict__ eattr, const int* __restrict__ src,
                                       const int* __restrict__ dst, const __nv_bfloat16* __restrict__ w_e,
                                       const __nv_bfloat16* __restrict__ w_x, __nv_bfloat16* __restrict__ out,
                                       int node0, int nvalid, uint32_t ident) {
    const int tid = threadIdx.x, lane = tid & 31, warp = tid >> 5, g = lane >> 2, t = lane & 3;
    float* acc = sc->acc + blockIdx.x * 384 * 68;
    for (int i = tid; i < 384 * 68; i += NT) __stcg(acc + i, 0.f);
    __threadfence();
    __syncthreads();
    const uint32_t* sA = reinterpret_cast<const uint32_t*>(smem + SM_H);
    const __nv_bfloat16* sP = reinterpret_cast<const __nv_bfloat16*>(smem + SM_POS);
    const unsigned short* pos16 = reinterpret_cast<const unsigned short*>(pos);
    const float wd0 = __bfloat162float(w_e[128 * 64 + 2 * lane]), wd1 = __bfloat162float(w_e[128 * 64 + 2 * lane + 1]);
    const float wa0 = __bfloat162float(w_e[129 * 64 + 2 * lane]), wa1 = __bfloat162float(w_e[129 * 64 + 2 * lane + 1]);
    const float wx0 = __bfloat162float(w_x[2 * lane]), wx1 = __bfloat162float(w_x[2 * lane + 1]);
    for (int eb = warp * 32; eb < EE; eb += NT) {
        const int dv = dst[eb + lane] - node0;
        unsigned mask = __ballot_sync(~0u, dv >= 0 && dv < nvalid);
        while (mask) {
            const int l = __ffs(mask) - 1;
            mask &= mask - 1;
            const int dl = __shfl_sync(~0u, dv, l);
            const int s = src[eb + l];
            const uint32_t av = sA[dl * 32 + (lane ^ ((dl & 1) << 4))];
            const uint32_t bv = __ldcg(reinterpret_cast<const uint32_t*>(sc->B) + (size_t)s * 32 + ((lane >> 2) & 3) * 8 + (lane >> 4) * 4 + (lane & 3));
            const uint32_t pdxy = *reinterpret_cast<const uint32_t*>(sP + dl * 4);
            const uint32_t pdz = *reinterpret_cast<const uint32_t*>(sP + dl * 4 + 2);
            const uint32_t psxy = pos16[s * 3] | ((uint32_t)pos16[s * 3 + 1] << 16), psz = pos16[s * 3 + 2];
            const uint32_t dxy = hsub2_bf16(pdxy, psxy), dz = hsub2_bf16(pdz, psz);
            const uint32_t sxy = hmul2_bf16(dxy, dxy), sz = hmul2_bf16(dz, dz);
            const float d2 = bf_lo(sxy) + bf_hi(sxy) + bf_lo(sz);
            const float ev = __bfloat162float(eattr[eb + l]);
            const float h0 = 0.5f * (d2 * wd0 + ev * wa0) + bf_lo(bv) + bf_lo(av);
            const float h1 = 0.5f * (d2 * wd1 + ev * wa1) + bf_hi(bv) + bf_hi(av);
            const uint32_t mp = pack_bf16(silu_half(h0), silu_half(h1));
            float cs = bf_lo(mp) * wx0 + bf_hi(mp) * wx1;
#pragma unroll
            for (int o = 16; o >= 1; o >>= 1) cs += __shfl_xor_sync(~0u, cs, o);
            atomicAdd(&acc[dl * 68 + 2 * lane], bf_lo(mp));
            atomicAdd(&acc[dl * 68 + 2 * lane + 1], bf_hi(mp));
            if (lane < 3) atomicAdd(&acc[dl * 68 + 64 + lane], cs * (lane == 0 ? bf_lo(dxy) : lane == 1 ? bf_hi(dxy) : bf_lo(dz)));
        }
    }
    __threadfence();
    __syncthreads();
    for (int i = tid; i < nvalid * 3; i += NT)
        out[(size_t)NN * 64 + node0 * 3 + i] = __float2bfloat16(__bfloat162float(sP[(i / 3) * 4 + i % 3]) + __ldcg(acc + (i / 3) * 68 + 64 + i % 3));
    for (int gi = warp; gi < NG; gi += NW) {
        const int n = gi * 8 + g;
        uint32_t m[8];
#pragma unroll
        for (int j = 0; j < 8; j++) {
            const int f = 8 * t + 2 * (j & 3) + 32 * (j >> 2);
            m[j] = pack_bf16(__ldcg(acc + n * 68 + f), __ldcg(acc + n * 68 + f + 1));
        }
        node_update(smem, m, n, nvalid, node0, ident, h, out);
    }
}

constexpr int BAR_E = 1;
constexpr int BAR_GO = 2;
constexpr int BAR_FREE = 3;
constexpr int BAR_S1 = 4;
constexpr int BAR_C = 5;
constexpr int BAR_B = 6;
constexpr int BAR_PRIO = 8;
constexpr int BAR_OFF = 9;
constexpr int BAR_G = 7;

__global__ void __launch_bounds__(NT, 1)
egnn_kernel(const __nv_bfloat16* __restrict__ h, const __nv_bfloat16* __restrict__ pos,
            const __nv_bfloat16* __restrict__ eattr, const int* __restrict__ src, const int* __restrict__ dst,
            const __nv_bfloat16* __restrict__ w_e, const __nv_bfloat16* __restrict__ w_x,
            const __nv_bfloat16* __restrict__ w_h, __nv_bfloat16* __restrict__ out, Scratch* sc) {
    extern __shared__ __align__(1024) unsigned char smem[];
    const int tid = threadIdx.x, lane = tid & 31, warp = tid >> 5;
    const int g = lane >> 2, t = lane & 3;
    const int b = blockIdx.x;
    const int node0 = b * NPB;
    const int nvalid = min(NPB, NN - node0);
    const uint32_t sb = smem_u32(smem);

    uint32_t* sHist = reinterpret_cast<uint32_t*>(smem + SM_HIST);
    uint32_t* sCur = reinterpret_cast<uint32_t*>(smem + SM_CUR);
    uint32_t* sDh = reinterpret_cast<uint32_t*>(smem + SM_DH);
    uint32_t* sOrd = reinterpret_cast<uint32_t*>(smem + SM_ORD);
    uint32_t* sMisc = reinterpret_cast<uint32_t*>(smem + SM_MISC);
    uint32_t* sSlot = reinterpret_cast<uint32_t*>(smem + SM_SLOT);
    uint32_t* sTag = reinterpret_cast<uint32_t*>(smem + SM_TAG);
    STAMP(0);

    const int e0 = b * EPB;
    const int nchunk = (min(EPB, EE - e0)) >> 2;
    const int clast = min(tid + NTE * (RND - 1), nchunk - 1);
    const int4* wg = reinterpret_cast<const int4*>((warp & 2) ? w_h : w_e) + (warp & 1) * 512 + lane;
    int4 vd[RND];
#pragma unroll
    for (int j = 0; j < RND; j++)
        vd[j] = ldg_stream4(warp < NWE ? reinterpret_cast<const int4*>(dst + e0) + (j < RND - 1 ? tid + NTE * j : clast) : wg + 32 * j);

    const uint32_t launch = ld_relaxed(&sc->sync[0]);
    int4 wv[12];
    if (warp >= NWE) {
#pragma unroll
        for (int j = 0; j < 12; j++) wv[j] = ldg_stream4(wg + 32 * (j + RND));
    }

    if (__builtin_expect(warp < NWE, 1)) {
        if (tid < 60) reinterpret_cast<uint4*>(sHist)[tid] = make_uint4(0, 0, 0, 0);
        sCur[tid] = tid ? sb + SM_SLOT + (tid - 1) * (CAPD * 4) : sb + SM_HIST;
#pragma unroll
        for (int j = 0; j < 3; j++) reinterpret_cast<uint2*>(smem + SM_IDX)[tid + NTE * j] = make_uint2(0, 0);
        if (tid < 32) sCur[384 + tid] = sb + SM_HIST;
#pragma unroll
        for (int j = 0; j < RND; j++) {
            const int c = j < RND - 1 ? tid + NTE * j : clast;
            asm volatile("cp.async.cg.shared.global [%0], [%1], 16;" :: "r"(sb + SM_SRC + (tid + NTE * j) * 16), "l"(reinterpret_cast<const int4*>(src + e0) + c) : "memory");
            asm volatile("cp.async.ca.shared.global [%0], [%1], 8;" :: "r"(sb + SM_EA + (tid + NTE * j) * 8), "l"(reinterpret_cast<const uint2*>(eattr + e0) + c) : "memory");
        }
        bar_sync(BAR_E, NTE);
        uint32_t ha[4 * RND], rk[4 * RND], dl[4 * RND];
#pragma unroll
        for (int j = 0; j < RND; j++) {
            const int dv[4] = {vd[j].x, vd[j].y, vd[j].z, vd[j].w};
#pragma unroll
            for (int i = 0; i < 4; i++) {
                uint32_t own = __umulhi((uint32_t)dv[i], 11332368u);
                dl[j * 4 + i] = (uint32_t)dv[i] + 1 - own * NPB;
                if (j == RND - 1 && tid + NTE * j >= nchunk) own = NB + (lane & 15);
                ha[j * 4 + i] = sb + SM_HIST + own * 4;
                rk[j * 4 + i] = atoms_add(ha[j * 4 + i], 21846);
            }
        }
        STAMP(1);
        bar_arrive(BAR_GO, NT);
        const uint32_t tag = (launch % 31u + 1) << 27, lid = launch + 1, target = lid * NB;
        unsigned spin = 0;
        auto poll_all = [&](int which) {
            while ((int)(ld_relaxed(&sc->sync[which]) - target) < 0 && ++spin < SPIN_LIMIT) __nanosleep(40);
        };
        auto count = [&](int which) { asm volatile("red.relaxed.gpu.global.add.u32 [%0], 1;" :: "l"(&sc->sync[which]) : "memory"); };
        bar_sync(BAR_OFF, NTE + 32);
        STAMP(2);
#pragma unroll
        for (int i = 0; i < 4 * RND; i++) rk[i] = (rk[i] >> 14) + lds_u32(ha[i]);
#pragma unroll
        for (int i = 0; i < 4 * RND; i++)
            asm volatile("red.shared.add.u32 [%0], %1;" :: "r"(sb + SM_IDX + (rk[i] & ~3u)), "r"(dl[i] << ((rk[i] & 3) * 9)) : "memory");
        bar_sync(BAR_E, NTE);
#pragma unroll
        for (int j = 0; j < 6; j++) sSlot[(tid + NTE * j) * 4 + 3] = reinterpret_cast<const uint32_t*>(smem + SM_IDX)[tid + NTE * j] | tag;
        STAMP(12);
        asm volatile("cp.async.wait_all;" ::: "memory");
        STAMP(4);
        {
            int4 vs[RND];
            uint2 ve[RND];
#pragma unroll
            for (int j = 0; j < RND; j++) {
                vs[j] = reinterpret_cast<const int4*>(smem + SM_SRC)[tid + NTE * j];
                ve[j] = reinterpret_cast<const uint2*>(smem + SM_EA)[tid + NTE * j];
            }
#pragma unroll
            for (int j = 0; j < RND; j++) {
                sts_u32(sb + SM_SLOT + rk[j * 4] * 4, __byte_perm(vs[j].x, ve[j].x, 0x5410));
                sts_u32(sb + SM_SLOT + rk[j * 4 + 1] * 4, __byte_perm(vs[j].y, ve[j].x, 0x7610));
                sts_u32(sb + SM_SLOT + rk[j * 4 + 2] * 4, __byte_perm(vs[j].z, ve[j].y, 0x5410));
                sts_u32(sb + SM_SLOT + rk[j * 4 + 3] * 4, __byte_perm(vs[j].w, ve[j].y, 0x7610));
            }
        }
        fence_async_smem();
        STAMP(3);
        if (warp == NWC) {
            bar_sync(BAR_S1, NTE);
            if (lane == 0) bulk_s2g(sc->rec + b * RU, sb + SM_SLOT, RU * 16);
            __syncwarp();
            bar_arrive(BAR_PRIO, 160);
            if (lane == 0) bulk_wait();
            __syncwarp();
            bar_arrive(BAR_FREE, NTE);
            STAMPW(NWC, 17);
            {
                const unsigned short* we = reinterpret_cast<const unsigned short*>(w_e) + (t < 3 ? 128 : 129) * 64;
                const uint32_t* wx = reinterpret_cast<const uint32_t*>(w_x);
                uint32_t c[12];
#pragma unroll
                for (int j = 0; j < 4; j++) {
                    const int fc = 8 * (g >> 1) + 4 * (j & 1) + (g & 1) + 32 * (j >> 1);
                    const uint32_t w = (uint32_t)__ldg(we + fc) | ((uint32_t)__ldg(we + fc + 2) << 16);
                    c[j] = hmul2_bf16(w, t < 3 ? 0x3f003f00u : 0xbf00bf00u);
                    const uint32_t x = __ldg(wx + 4 * t + 2 * (j & 1) + (g & 1) + 16 * (j >> 1));
                    c[4 + 2 * j] = (g & 2) ? 0u : x;
                    c[5 + 2 * j] = (g & 2) ? x : 0u;
                }
#pragma unroll
                for (int j = 0; j < 3; j++)
                    reinterpret_cast<uint4*>(smem + SM_CONST)[j * 32 + lane] = make_uint4(c[4 * j], c[4 * j + 1], c[4 * j + 2], c[4 * j + 3]);
                const uint32_t id = ((2 * t == g) ? 0x3f80u : 0u) | ((2 * t + 1 == g) ? 0x3f800000u : 0u);
                reinterpret_cast<uint4*>(smem + SM_CONST)[96 + lane] = make_uint4(id, id, 0u, 0u);
                reinterpret_cast<uint4*>(smem + SM_CONST)[128 + lane] =
                    make_uint4(t < 3 ? 0xffffffffu : 0u, (t & 1) ? 0x3244u : 0x1044u, (t & 1) ? 0x1044u : 0x3244u, 0u);
                reinterpret_cast<ulonglong2*>(smem + SM_CONST)[160 + lane] =
                    make_ulonglong2(reinterpret_cast<unsigned long long>(sc->B) + t * 32, reinterpret_cast<unsigned long long>(sc->pos) + t * 2);
            }
            bar_sync(BAR_B, 160);
            if (lane == 0) {
                fence_gpu();
                count(2);
                STAMPW(NWC, 18);
                {
                    uint32_t v;
                    do {
                        asm volatile("ld.acquire.gpu.global.u32 %0, [%1];" : "=r"(v) : "l"(&sc->sync[2]) : "memory");
                    } while ((int)(v - target) < 0 && ++spin < SPIN_LIMIT);
                }
                if (b == 0) st_relaxed(&sc->sync[0], lid);
            }
            STAMPW(NWC, 19);
        } else {
            bar_arrive(BAR_S1, NTE);
            const uint2* fp = sc->flag + b * 160 + warp * NSEG + min(lane, NSEG - 1);
            uint2 fv = ld_relaxed64(fp);
            if (__any_sync(~0u, fv.y != lid)) {
                poll_all(1);
                do { fv = ld_relaxed64(fp); } while (__any_sync(~0u, fv.y != lid) && ++spin < SPIN_LIMIT);
            }
            STAMP(22);
            const uint32_t np = (lane < NSEG && fv.y == lid) ? fv.x >> 16 : 0u;
            uint32_t inc = np;
#pragma unroll
            for (int o = 1; o < 16; o <<= 1) { const uint32_t v = __shfl_up_sync(~0u, inc, o); if (lane >= o) inc += v; }
            const uint32_t first = np ? inc - np : 0xffffffffu;
            const uint32_t total = __shfl_sync(~0u, inc, NSEG - 1);
            const uint32_t delta = (warp * NSEG + lane) * RU + (fv.x & 0xffff) - first;
#pragma unroll 1
            for (uint32_t r0 = 0; r0 == 0 || r0 * 32 < total; r0 += NRD) {
                const uint4* ad[NRD];
                const uint32_t fr = (first >> 5) - r0;
                const uint32_t cum = (__reduce_add_sync(~0u, fr < NRD ? 16u << (4 * fr) : (first >> 5) < r0 ? 1u : 0u)) * 0x11111111u;
#pragma unroll
                for (int i = 0; i < NRD; i++) {
                    const uint32_t starts = __reduce_or_sync(~0u, fr == i ? 1u << (first & 31) : 0u);
                    const uint32_t seg = ((cum >> (4 * i)) & 15) + __popc(starts & (0xffffffffu >> (31 - lane))) - 1;
                    ad[i] = sc->rec + (__shfl_sync(~0u, delta, seg) + min((r0 + i) * 32 + lane, total - 1));
                }
                if (r0 == 0) {
                    STAMP(23);
                    bar_sync(BAR_FREE, NTE);
                    for (int i = tid; i < 384 * CAPD / 4; i += NWC * 32)
                        reinterpret_cast<uint4*>(sSlot)[i] = make_uint4(NN, NN, NN, NN);
                    bar_sync(BAR_C, NWC * 32);
                    __nanosleep(100);
                    STAMP(9);
                    if (total == 0) break;
                }
                uint4 q[NRD];
                bool wait;
                do {
                    uint32_t bad = 0;
#pragma unroll
                    for (int i = 0; i < NRD; i++) q[i] = ld_relaxed128(ad[i]);
#pragma unroll
                    for (int i = 0; i < NRD; i++) bad |= q[i].w ^ tag;
                    wait = __any_sync(~0u, bad >> 27);
                } while (wait && ++spin < SPIN_LIMIT);
                STAMP(21);
                if (wait) break;
                uint32_t wa[3 * NRD];
#pragma unroll
                for (int i = 0; i < NRD; i++) {
                    if (i == NRD - 1 && (r0 + i) * 32 >= total) break;
                    const bool ok = (r0 + i) * 32 + lane < total;
                    const uint32_t cb = ok ? sb + SM_CUR : sb + SM_CUR + (384 + lane) * 4, w = ok ? q[i].w : 0u;
                    wa[3 * i] = atoms_add(cb + ((w << 2) & 0x7fc), 4);
                    wa[3 * i + 1] = atoms_add(cb + ((w >> 7) & 0x7fc), 4);
                    wa[3 * i + 2] = atoms_add(cb + ((w >> 16) & 0x7fc), 4);
                }
#pragma unroll
                for (int i = 0; i < NRD; i++) {
                    if (i == NRD - 1 && (r0 + i) * 32 >= total) break;
                    sts_u32(min(wa[3 * i], sb + SM_HIST + lane * 4), q[i].x);
                    sts_u32(min(wa[3 * i + 1], sb + SM_HIST + lane * 4), q[i].y);
                    sts_u32(min(wa[3 * i + 2], sb + SM_HIST + lane * 4), q[i].z);
                }
            }
            STAMP(10);
            if (warp < 6) {
                bar_sync(BAR_C, NWC * 32);
                uint32_t dg[2], qq[2];
#pragma unroll
                for (int k = 0; k < 2; k++) {
                    dg[k] = tid + 192 * k < NPB ? (sCur[tid + 192 * k + 1] - (sb + SM_SLOT)) / 4 - (tid + 192 * k) * CAPD : 0u;
                    if (dg[k] > CAPD) { sMisc[0] = 1; dg[k] = CAPD; }
                }
#pragma unroll
                for (int k = 0; k < 2; k++) qq[k] = atomicAdd(&sDh[dg[k]], 1u);
                bar_sync(BAR_E, 192);
                const uint2 c2 = *reinterpret_cast<const uint2*>(sDh + 62 - 2 * lane);
                uint32_t inc2 = c2.x + c2.y;
#pragma unroll
                for (int o = 1; o < 32; o <<= 1) { const uint32_t v = __shfl_up_sync(~0u, inc2, o); if (lane >= o) inc2 += v; }
#pragma unroll
                for (int k = 0; k < 2; k++) {
                    const uint32_t pk = __shfl_sync(~0u, (inc2 - c2.x) | ((inc2 - c2.x - c2.y) << 16), (63 - dg[k]) >> 1);
                    sOrd[((dg[k] & 1) ? pk >> 16 : pk & 0xffff) + qq[k]] = (tid + 192 * k) | (dg[k] << 16);
                }
            } else {
                bar_arrive(BAR_C, NWC * 32);
            }
            STAMP(11);
        }
    } else {
        const int aw = warp - NWE, at = tid - NTE;
        const uint4* hg = reinterpret_cast<const uint4*>(h + (size_t)node0 * 64) + at;
        const uint32_t hs = sb + SM_H + ((at ^ ((at >> 3) & 7)) << 4);
        auto load_tile = [&](int tile) {
#pragma unroll
            for (int k = 0; k < 4; k++)
                if (tile * 512 + k * 128 + at < nvalid * 8)
                    asm volatile("cp.async.cg.shared.global [%0], [%1], 16;" :: "r"(hs + tile * 8192 + k * 2048), "l"(hg + tile * 512 + k * 128));
            asm volatile("cp.async.commit_group;" ::: "memory");
        };
        uint32_t op[3][3];
        {
#pragma unroll
            for (int j = 0; j < 3; j++) {
                const unsigned short* pg = reinterpret_cast<const unsigned short*>(pos) + (size_t)(node0 + min(at + 128 * j, nvalid - 1)) * 3;
                op[j][0] = __ldg(pg); op[j][1] = __ldg(pg + 1); op[j][2] = __ldg(pg + 2);
            }
            if (at < 2) sTag[at] = NN;
            int ch = lane & 7;
            if (aw == 1) ch = ((ch & 3) << 1) | (ch >> 2);
            const int rr = lane >> 3;
            uint32_t* sw = reinterpret_cast<uint32_t*>(smem + (aw == 3 ? SM_W2 : SM_W + ((aw + 2) % 3) * 8192)) + rr * 32 + (ch & 3);
#pragma unroll
            for (int j = 0; j < 16; j++) {
                const int4 w = j < RND ? vd[j] : wv[j < RND ? 0 : j - RND];
                const int x = (ch & 4) ^ (aw == 3 ? ((((j >> 1) & 3) << 1) | (rr & 1)) : (rr | ((j & 1) << 2)));
                sw[j * 128 + ((x ^ 0) << 2)] = half_bf16x2(w.x);
                sw[j * 128 + ((x ^ 1) << 2)] = half_bf16x2(w.y);
                sw[j * 128 + ((x ^ 2) << 2)] = half_bf16x2(w.z);
                sw[j * 128 + ((x ^ 3) << 2)] = half_bf16x2(w.w);
            }
            fence_async_smem();
        }
        STAMPW(NWE + 2, 20);
        bar_sync(BAR_GO, NT);
        if (aw == 0) {
            uint32_t pc[5], s = 0;
#pragma unroll
            for (int i = 0; i < 5; i++) { pc[i] = max((sHist[lane * 5 + i] + 43692u) >> 16, 1u); s += pc[i]; }
            uint32_t inc = s;
#pragma unroll
            for (int o = 1; o < 32; o <<= 1) { const uint32_t v = __shfl_up_sync(~0u, inc, o); if (lane >= o) inc += v; }
            uint32_t off = inc - s;
#pragma unroll
            for (int i = 0; i < 5; i++) { sHist[lane * 5 + i] = off * 4; off += pc[i]; }
            bar_arrive(BAR_OFF, NTE + 32);
#pragma unroll
            for (int k = 0; k < HWIN; k++) load_tile(k);
#pragma unroll
            for (int i = 4; i >= 0; i--) {
                off -= pc[i];
                if (lane * 5 + i < NB) st_relaxed64(sc->flag + (lane * 5 + i) * 160 + b, off | (pc[i] << 16), launch + 1);
            }
            __syncwarp();
            if (lane == 0) asm volatile("red.relaxed.gpu.global.add.u32 [%0], 1;" :: "l"(&sc->sync[1]) : "memory");
        } else {
#pragma unroll
            for (int k = 0; k < HWIN; k++) load_tile(k);
        }
#pragma unroll
        for (int j = 0; j < 3; j++) {
            const int n = at + 128 * j;
            const uint2 v = make_uint2(op[j][0] | (op[j][1] << 16), op[j][2]);
            *reinterpret_cast<uint2*>(smem + SM_POS + n * 8) = v;
            if (n < nvalid) sc->pos[node0 + n] = v;
        }
        if (b == 0 && at < 8) sc->B[NN * 8 + at] = make_uint4(0xf149f149u, 0xf149f149u, 0xf149f149u, 0xf149f149u);
        if (b == 0 && at >= 8 && at < 12) sc->pos[NN + at - 8] = make_uint2(0, 0);

        const uint64_t dw = wg_desc(sb + SM_W);
        auto piece = [&](const float (&o)[32], int half, int up) {
            return make_uint4(pack_bf16(o[16 * half + 2 * up], o[16 * half + 2 * up + 1]), pack_bf16(o[16 * half + 4 + 2 * up], o[16 * half + 5 + 2 * up]),
                              pack_bf16(o[16 * half + 8 + 2 * up], o[16 * half + 9 + 2 * up]), pack_bf16(o[16 * half + 12 + 2 * up], o[16 * half + 13 + 2 * up]));
        };
        auto issue = [&](float (&o)[32], int tile, int mat) {
            const uint64_t da = wg_desc(sb + SM_H + tile * 8192);
            asm volatile("wgmma.fence.sync.aligned;" ::: "memory");
#pragma unroll
            for (int kk = 0; kk < 4; kk++) wgmma64(o, da + 2 * kk, dw + mat * 512 + 128 * kk, kk);
            asm volatile("wgmma.commit_group.sync.aligned;" ::: "memory");
        };
#define WG_WAIT(n, o) do { asm volatile("wgmma.wait_group.sync.aligned " #n ";" ::: "memory"); \
        _Pragma("unroll") for (int i_ = 0; i_ < 32; i_++) asm volatile("" : "+f"(o[i_]) :: "memory"); } while (0)
        auto store_s = [&](const float (&o)[32], int base, int tile) {
#pragma unroll
            for (int i = 0; i < 4; i++) *srow(smem + base, tile * 64 + aw * 16 + g + 8 * (i >> 1), t, i & 1) = piece(o, i & 1, i >> 1);
        };
        float o1[32], o2[32];
        auto stage_b = [&](const float (&o)[32], int slot) {
#pragma unroll
            for (int i = 0; i < 4; i++)
                reinterpret_cast<uint4*>(smem + SM_U + (slot * 64 + aw * 16 + g + 8 * (i >> 1)) * 128)[t + 4 * (i & 1)] = piece(o, i & 1, i >> 1);
        };
#pragma unroll 1
        for (int k0 = 0; k0 < 6; k0 += 3) {
#pragma unroll
            for (int k = 0; k < 3; k++) {
                asm volatile("cp.async.wait_group %0;" :: "n"(HWIN - 1) : "memory");
                load_tile(k0 + k + HWIN);
            }
            fence_async_smem();
            bar_sync(BAR_G, 128);
            STAMPW(NWE, 5 + k0 / 3);
            issue(o1, k0, 0);
            issue(o2, k0 + 1, 0);
            if (k0 == 0) bar_sync(BAR_PRIO, 160);
            else {
                if (at == 0) asm volatile("cp.async.bulk.wait_group.read 0;" ::: "memory");
                bar_sync(BAR_G, 128);
            }
            WG_WAIT(1, o1);
            stage_b(o1, 0);
            issue(o1, k0 + 2, 0);
            WG_WAIT(1, o2);
            stage_b(o2, 1);
            WG_WAIT(0, o1);
            stage_b(o1, 2);
            fence_async_smem();
            bar_sync(BAR_G, 128);
            if (at == 0) bulk_s2g(sc->B + (size_t)(node0 + k0 * 64) * 8, sb + SM_U, min(192, nvalid - k0 * 64) * 128);
        }
        STAMPW(NWE, 7);
        {
            issue(o2, 3, 1);
            issue(o1, 3, 2);
            WG_WAIT(1, o2);
            store_s(o2, SM_U, 3);
            issue(o2, 0, 1);
            WG_WAIT(1, o1);
            store_s(o1, SM_H, 3);
            issue(o1, 0, 2);
            if (at == 0) bulk_wait();
            __syncwarp();
            bar_arrive(BAR_B, 160);
            bar_sync(BAR_G, 128);
#pragma unroll
            for (int k = 0; k < 3; k++) {
                WG_WAIT(1, o2);
                store_s(o2, SM_U, k);
                issue(o2, k < 2 ? k + 1 : 5, 1);
                WG_WAIT(1, o1);
                store_s(o1, SM_H, k);
                issue(o1, k < 2 ? k + 1 : 4, k < 2 ? 2 : 1);
            }
            WG_WAIT(1, o2);
            uint4 uk[4];
#pragma unroll
            for (int i = 0; i < 4; i++) uk[i] = piece(o2, i & 1, i >> 1);
            issue(o2, 5, 2);
            WG_WAIT(1, o1);
            bar_sync(BAR_G, 128);
            store_s(o1, SM_U, 4);
            issue(o1, 4, 2);
            WG_WAIT(1, o2);
            store_s(o2, SM_H, 5);
            WG_WAIT(0, o1);
            store_s(o1, SM_H, 4);
            bar_sync(BAR_G, 128);
#pragma unroll
            for (int i = 0; i < 4; i++) *srow(smem + SM_U, 5 * 64 + aw * 16 + g + 8 * (i >> 1), t, i & 1) = uk[i];
        }
        STAMPW(NWE, 8);
    }

    __syncthreads();
    uint32_t wda[4], wxr[4][2], ident, ident2, sqmask, selown, seloth;
    {
        const uint4* cp = reinterpret_cast<const uint4*>(smem + SM_CONST) + lane;
        const uint4 c0 = cp[0], c1 = cp[32], c2 = cp[64], c3 = cp[96], c4 = cp[128];
        wda[0] = c0.x; wda[1] = c0.y; wda[2] = c0.z; wda[3] = c0.w;
        wxr[0][0] = c1.x; wxr[0][1] = c1.y; wxr[1][0] = c1.z; wxr[1][1] = c1.w;
        wxr[2][0] = c2.x; wxr[2][1] = c2.y; wxr[3][0] = c2.z; wxr[3][1] = c2.w;
        ident = c3.x; ident2 = c3.y; sqmask = c4.x; selown = c4.y; seloth = c4.z;
    }
    if (sMisc[0]) {
        slow_path(sc, smem, h, pos, eattr, src, dst, w_e, w_x, out, node0, nvalid, ident);
        return;
    }

    const ulonglong2 bases = reinterpret_cast<const ulonglong2*>(smem + SM_CONST)[160 + lane];
    const unsigned long long bbase = bases.x, pbase = bases.y;
    uint4 a0, a1, b0, b1;
    uint32_t psA, psB, e2;
    uint32_t og[3];
#pragma unroll
    for (int k = 0; k < 3; k++) {
        const int gi = k == 0 ? warp : (k + 1) * NW - 1 - warp;
        const uint32_t o = sOrd[gi * 8 + g];
        const uint32_t len = max(sOrd[gi * 8] >> 16, 1u);
        og[k] = (o & 0xffff) | (len << 16);
    }
    auto gather = [&](uint4& lo, uint4& hi, uint32_t& ps, uint32_t sw) {
        asm volatile("{\n\t.reg .u32 s;\n\t.reg .u64 a, c;\n\t"
                     "and.b32 s, %9, 0xffff;\n\t"
                     "mad.wide.u32 a, s, 128, %10;\n\t"
                     "mad.wide.u32 c, s, 8, %11;\n\t"
                     "ld.global.v4.u32 {%0,%1,%2,%3}, [a];\n\t"
                     "ld.global.L1::evict_first.v4.u32 {%4,%5,%6,%7}, [a+16];\n\t"
                     "ld.global.u16 %8, [c];\n\t}"
                     : "=r"(lo.x), "=r"(lo.y), "=r"(lo.z), "=r"(lo.w), "=r"(hi.x), "=r"(hi.y), "=r"(hi.z), "=r"(hi.w), "=r"(ps)
                     : "r"(sw), "l"(bbase), "l"(pbase));
    };
    auto lds64 = [&](uint32_t addr) -> uint2 {
        uint2 v;
        asm volatile("ld.shared.v2.u32 {%0,%1}, [%2];" : "=r"(v.x), "=r"(v.y) : "r"(addr) : "memory");
        return v;
    };
    uint32_t sp = sb + SM_SLOT + (og[0] & 0xffff) * (CAPD * 4);
    STAMP(13);
    {
        const uint2 sw = lds64(sp);
        gather(a0, a1, psA, sw.x);
        gather(b0, b1, psB, sw.y);
        e2 = __byte_perm(sw.x, sw.y, 0x7632);
    }
#pragma unroll 1
    for (int k = 0; k < 3; k++) {
        const int n = og[0] & 0xffff, len = og[0] >> 16;
        const uint32_t spn = k < 2 ? sb + SM_SLOT + (og[1] & 0xffff) * (CAPD * 4) : sb + SM_TAG;
        og[0] = og[1];
        og[1] = og[2];
        float ci[4][4], acc[4][4];
        {
            uint32_t ar[8];
            load_srow(ar, smem + SM_H, n, t);
#pragma unroll
            for (int j = 0; j < 4; j++) {
                ci[j][0] = bf_lo(ar[2 * j]); ci[j][1] = bf_hi(ar[2 * j]);
                ci[j][2] = bf_lo(ar[2 * j + 1]); ci[j][3] = bf_hi(ar[2 * j + 1]);
                acc[j][0] = acc[j][1] = acc[j][2] = acc[j][3] = 0.f;
            }
        }
        const uint32_t pd2 = lds_u16(sb + SM_POS + n * 8 + 2 * t) * 0x10001u;
        float px = 0.f;
        float c0p = 0.f, c3p = 0.f;
        uint32_t dfp = 0;
        auto flush = [&]() {
            const float own = c0p + c3p;
            const float oth = __shfl_xor_sync(~0u, own, 1);
            px = fmaf(__uint_as_float(__byte_perm(dfp, 0, selown)), own, px);
            px = fmaf(__uint_as_float(__byte_perm(dfp, 0, seloth)), oth, px);
        };
        auto step = [&](auto both) {
            constexpr bool BOTH = decltype(both)::value;
            const uint2 sw = lds64(sp);
            const uint32_t ps2 = __byte_perm(psA, psB, 0x5410) | (e2 & ~sqmask);
            const uint32_t df = hsub2_bf16(pd2, ps2);
            const uint32_t x2 = hmul2_bf16(df, (df & sqmask) | (0x3f803f80u & ~sqmask));
            const uint32_t ra[8] = {a0.x, a0.y, a0.z, a0.w, a1.x, a1.y, a1.z, a1.w};
            const uint32_t rb[8] = {b0.x, b0.y, b0.z, b0.w, b1.x, b1.y, b1.z, b1.w};
            float da[4][4], db[4][4];
            auto loads = [&]() {
                gather(a0, a1, psA, sw.x);
                gather(b0, b1, psB, sw.y);
                e2 = __byte_perm(sw.x, sw.y, 0x7632);
            };
            if (K_AB) {
#pragma unroll
                for (int j = 0; j < 4; j++) mma8(da[j], x2 & 0xffffu, x2 << 16, wda[j], ci[j]);
#pragma unroll
                for (int j = 0; j < 4; j++) if (BOTH) mma8(db[j], x2 >> 16, x2 & 0xffff0000u, wda[j], ci[j]);
            } else {
#pragma unroll
                for (int j = 0; j < 4; j++) {
                    mma8(da[j], x2 & 0xffffu, x2 << 16, wda[j], ci[j]);
                    if (BOTH) mma8(db[j], x2 >> 16, x2 & 0xffff0000u, wda[j], ci[j]);
                }
            }
#pragma unroll
            for (int j = 0; j < 4; j++) {
                mma8_acc(da[j], ra[2 * j], ra[2 * j + 1], ident);
                if (BOTH) mma8_acc(db[j], rb[2 * j], rb[2 * j + 1], ident);
            }
            if (K_LD == 0) loads();
            float cs[2][4] = {{0.f, 0.f, 0.f, 0.f}, {0.f, 0.f, 0.f, 0.f}};
#pragma unroll
            for (int jj = 0; jj < 4; jj++) {
                const int j = (K_PJ >> (4 * jj)) & 3;
                const int c = K_CS == 0 ? (jj & 1) : (jj >> 1);
                uint32_t m0, m1, m2 = 0, m3 = 0;
                if (K_BF && BOTH) {
                    m2 = pack_bf16(silu_half(db[j][0]), silu_half(db[j][1]));
                    m3 = pack_bf16(silu_half(db[j][2]), silu_half(db[j][3]));
                }
                m0 = pack_bf16(silu_half(da[j][0]), silu_half(da[j][1]));
                m1 = pack_bf16(silu_half(da[j][2]), silu_half(da[j][3]));
                if (!K_BF && BOTH) {
                    m2 = pack_bf16(silu_half(db[j][0]), silu_half(db[j][1]));
                    m3 = pack_bf16(silu_half(db[j][2]), silu_half(db[j][3]));
                }
                if (BOTH) {
                    if (K_AC) mma16_acc(acc[j], m0, m1, m2, m3, ident, ident2);
                    mma16_acc(cs[c], m0, m1, m2, m3, wxr[j][0], wxr[j][1]);
                    if (!K_AC) mma16_acc(acc[j], m0, m1, m2, m3, ident, ident2);
                } else {
                    mma8_acc(acc[j], m0, m1, ident);
                    mma8_acc(cs[0], m0, m1, wxr[j][0]);
                }
                if (K_LD == jj + 1) loads();
            }
            if (K_SUM) { c0p = cs[0][0] + cs[1][0]; c3p = cs[0][3] + cs[1][3]; }
            else { c0p = cs[0][0] + cs[0][3]; c3p = cs[1][0] + cs[1][3]; }
            dfp = df;
            flush();
        };
        const uint32_t spe = sp + ((len - 1) >> 1) * 8;
#pragma unroll 1
        while (sp != spe) {
            sp += 8;
            step(std::true_type());
        }
        sp = spn;
        if (len & 1) step(std::false_type());
        else step(std::true_type());
        {
            if (t < 3 && n < nvalid) out[(size_t)NN * 64 + (node0 + n) * 3 + t] = __float2bfloat16(bf_lo(pd2) + px);
            uint32_t m[8];
#pragma unroll
            for (int j = 0; j < 4; j++) { m[2 * j] = pack_bf16(acc[j][0], acc[j][1]); m[2 * j + 1] = pack_bf16(acc[j][2], acc[j][3]); }
            node_update(smem, m, n, nvalid, node0, ident, h, out);
        }
    }
}

__global__ void fb_zero(Scratch* sc) {
    for (int i = blockIdx.x * blockDim.x + threadIdx.x; i < NN * 68; i += gridDim.x * blockDim.x) sc->acc[i] = 0.f;
}
__global__ void fb_edges(const __nv_bfloat16* __restrict__ h, const __nv_bfloat16* __restrict__ pos,
                         const __nv_bfloat16* __restrict__ eattr, const int* __restrict__ src, const int* __restrict__ dst,
                         const __nv_bfloat16* __restrict__ w_e, const __nv_bfloat16* __restrict__ w_x, Scratch* sc) {
    const int lane = threadIdx.x & 31;
    const uint32_t* w32 = reinterpret_cast<const uint32_t*>(w_e);
    for (int e = (blockIdx.x * blockDim.x + threadIdx.x) >> 5; e < EE; e += (gridDim.x * blockDim.x) >> 5) {
        const int s = src[e], d = dst[e];
        float df[3], d2 = 0.f;
        for (int c = 0; c < 3; c++) {
            df[c] = __bfloat162float(__hsub(pos[d * 3 + c], pos[s * 3 + c]));
            d2 += __bfloat162float(__float2bfloat16(df[c] * df[c]));
        }
        float x0 = 0.f, x1 = 0.f;
        for (int k = 0; k < 130; k++) {
            const float v = k < 64 ? __bfloat162float(h[d * 64 + k]) : k < 128 ? __bfloat162float(h[s * 64 + k - 64])
                                                                              : k == 128 ? d2 : __bfloat162float(eattr[e]);
            x0 = fmaf(v, bf_lo(w32[k * 32 + lane]), x0);
            x1 = fmaf(v, bf_hi(w32[k * 32 + lane]), x1);
        }
        const uint32_t m = pack_bf16(silu_half(0.5f * x0), silu_half(0.5f * x1));
        float cs = bf_lo(m) * __bfloat162float(w_x[2 * lane]) + bf_hi(m) * __bfloat162float(w_x[2 * lane + 1]);
        for (int o = 16; o >= 1; o >>= 1) cs += __shfl_xor_sync(~0u, cs, o);
        atomicAdd(&sc->acc[d * 68 + 2 * lane], bf_lo(m));
        atomicAdd(&sc->acc[d * 68 + 2 * lane + 1], bf_hi(m));
        if (lane < 3) atomicAdd(&sc->acc[d * 68 + 64 + lane], cs * (lane == 0 ? df[0] : lane == 1 ? df[1] : df[2]));
    }
}
__global__ void fb_nodes(const __nv_bfloat16* __restrict__ h, const __nv_bfloat16* __restrict__ pos,
                         const __nv_bfloat16* __restrict__ w_h, const Scratch* sc, __nv_bfloat16* __restrict__ out) {
    const int n = blockIdx.x, f = threadIdx.x;
    float x = 0.f;
    for (int k = 0; k < 64; k++)
        x += __bfloat162float(h[n * 64 + k]) * __bfloat162float(w_h[k * 64 + f]) +
             __bfloat162float(__float2bfloat16(sc->acc[n * 68 + k])) * __bfloat162float(w_h[(64 + k) * 64 + f]);
    out[n * 64 + f] = __hadd(h[n * 64 + f], __float2bfloat16(silu_half(0.5f * x)));
    if (f < 3) out[(size_t)NN * 64 + n * 3 + f] = __float2bfloat16(__bfloat162float(pos[n * 3 + f]) + sc->acc[n * 68 + 64 + f]);
}

}

extern "C" void kernel_launch(void* const* d_in, const int* in_sizes, int n_in, void* d_out, int out_size) {
    (void)in_sizes; (void)n_in; (void)out_size;
    static Scratch* sc = nullptr;
    static bool resident = false;
    if (!sc) {
        int dev = 0, sms = 0, per_sm = 0;
        cudaGetDevice(&dev);
        cudaDeviceGetAttribute(&sms, cudaDevAttrMultiProcessorCount, dev);
        if (cudaFuncSetAttribute(egnn_kernel, cudaFuncAttributeMaxDynamicSharedMemorySize, SM_TOTAL + DBG_SMEM) == cudaSuccess)
            cudaOccupancyMaxActiveBlocksPerMultiprocessor(&per_sm, egnn_kernel, NT, SM_TOTAL + DBG_SMEM);
        resident = sms * per_sm >= NB;
        cudaGetSymbolAddress(reinterpret_cast<void**>(&sc), g_scratch);
    }
    const __nv_bfloat16* h = (const __nv_bfloat16*)d_in[0];
    const __nv_bfloat16* pos = (const __nv_bfloat16*)d_in[1];
    const __nv_bfloat16* ea = (const __nv_bfloat16*)d_in[2];
    const int* src = (const int*)d_in[3];
    const int* dst = (const int*)d_in[4];
    const __nv_bfloat16* w_e = (const __nv_bfloat16*)d_in[5];
    const __nv_bfloat16* w_x = (const __nv_bfloat16*)d_in[6];
    const __nv_bfloat16* w_h = (const __nv_bfloat16*)d_in[7];
    __nv_bfloat16* out = (__nv_bfloat16*)d_out;
    if (!resident) {
        fb_zero<<<256, 256, 0, cudaStreamPerThread>>>(sc);
        fb_edges<<<1024, 256, 0, cudaStreamPerThread>>>(h, pos, ea, src, dst, w_e, w_x, sc);
        fb_nodes<<<NN, 64, 0, cudaStreamPerThread>>>(h, pos, w_h, sc, out);
        return;
    }
    cudaLaunchConfig_t cfg = {};
    cfg.gridDim = dim3(NB);
    cfg.blockDim = dim3(NT);
    cfg.dynamicSmemBytes = SM_TOTAL + DBG_SMEM;
    cfg.stream = cudaStreamPerThread;
    cudaLaunchAttribute attr;
    attr.id = cudaLaunchAttributeCooperative;
    attr.val.cooperative = 1;
    cfg.attrs = &attr;
    cfg.numAttrs = 1;
    cudaLaunchKernelEx(&cfg, egnn_kernel, h, pos, ea, src, dst, w_e, w_x, w_h, out, sc);
}
```
